```python
import torch

def _softmax(x, axis=-1):
    return torch.softmax(x, dim=axis)
def _gelu(x):
    return torch.nn.functional.gelu(x, approximate="tanh")
def _silu(x):
    return torch.nn.functional.silu(x)
def _sigmoid(x):
    return torch.sigmoid(x)
def _layernorm(x, axis=-1, eps=1e-5):
    m = x.mean(dim=axis, keepdim=True)
    v = x.var(dim=axis, keepdim=True, unbiased=False)
    return (x - m) / torch.sqrt(v + eps)
def _scatter_add(tgt, idx, src, axis=0):
    return tgt.clone().index_add_(axis, idx, src)
def _segment_sum(src, seg, n):
    out = torch.zeros((n,) + src.shape[1:], dtype=src.dtype)
    return out.index_add_(0, seg, src)
def _pad(x, pw):
    flat = tuple(v for pair in reversed(pw) for v in pair)
    return torch.nn.functional.pad(x, flat)

kernel_name = 'concat_heads__linear_attn_block__mha_block__prompt'

def setup_inputs():

    _w = (lambda a: (lambda t: t.to(torch.bfloat16) if t.is_floating_point() else t)(torch.as_tensor(a)))
    def _A_setup():
        B, S, D = 1, 2048, 512
        return {
            "x": _w((lambda *s: torch.randn(*s, dtype=torch.bfloat16) * 0.05)(B, S, D)),
            "wqkv": _w((lambda *s: torch.randn(*s, dtype=torch.bfloat16) * 1.6)(D, 3 * D)),
            "wo": _w((lambda *s: torch.randn(*s, dtype=torch.bfloat16) * 0.05)(D, D)),
        }
    _A_in = _A_setup()

    def _B_setup():
        B, S, D, H = 1, 2048, 512, 32
        return {
            "x": _w((lambda *s: torch.randn(*s, dtype=torch.bfloat16) * 0.2)(B, S, D)),
            "wqkv": _w((lambda *s: torch.randn(*s, dtype=torch.bfloat16) * 0.2)(D, 3 * D)),
            "wo": _w((lambda *s: torch.randn(*s, dtype=torch.bfloat16) * 0.05)(D, D)),
        }
    _B_in = _B_setup()

    return {
        "A_x": _A_in["x"],
        "A_wqkv": _A_in["wqkv"],
        "A_wo": _A_in["wo"],
        "B_x": _B_in["x"],
        "B_wqkv": _B_in["wqkv"],
        "B_wo": _B_in["wo"],
    }

def reference(A_x, A_wqkv, A_wo, B_x, B_wqkv, B_wo):
    def _A_ref(x, wqkv, wo):
        B, S, D = x.shape
        H = 32; Dh = D // H
        qkv = (lambda x, *d: x.permute(*d))((x @ wqkv).reshape(B, S, 3, H, Dh), 2, 0, 3, 1, 4)
        q, k, v = qkv[0], qkv[1], qkv[2]
        phi = lambda t: torch.where(t > 0, t + 1, torch.exp(t)) + 1e-6
        pq, pk = phi(q), phi(k)
        kv = torch.einsum("bhsd,bhse->bhde", pk, v)
        z = torch.einsum("bhsd->bhd", pk)
        num = torch.einsum("bhqd,bhde->bhqe", pq, kv)
        den = torch.einsum("bhqd,bhd->bhq", pq, z)[..., None] + 1e-6
        o = num / den
        return (lambda x, *d: x.permute(*d))(o, 0, 2, 1, 3).reshape(B, S, D) @ wo

    def _B_ref(x, wqkv, wo):
        B, S, D = x.shape
        H = 32
        Dh = D // H
        qkv = (lambda x, *d: x.permute(*d))((x @ wqkv).reshape(B, S, 3, H, Dh), 2, 0, 3, 1, 4)
        q, k, v = qkv[0], qkv[1], qkv[2]
        scores = torch.einsum("bhqd,bhkd->bhqk", q, k) * (Dh ** -0.5)
        p = _softmax(scores, axis=-1)
        o = torch.einsum("bhqk,bhkd->bhqd", p, v)
        return (lambda x, *d: x.permute(*d))(o, 0, 2, 1, 3).reshape(B, S, D) @ wo

    a = _A_ref(A_x, A_wqkv, A_wo)
    b = _B_ref(B_x, B_wqkv, B_wo)
    return torch.concatenate([a, b], axis=-1)
```

```cpp
#include <cuda_runtime.h>
#include <cuda_bf16.h>
#include <cuda.h>
#include <stdint.h>

namespace {

constexpr int S_LEN = 2048;
constexpr int NH = 32;

__device__ __align__(1024) uint16_t g_qB[NH * S_LEN * 16];
__device__ __align__(1024) uint16_t g_kB[NH * S_LEN * 16];
__device__ __align__(1024) uint16_t g_vB[NH * S_LEN * 16];
__device__ __align__(1024) uint16_t g_qA[NH * S_LEN * 16];
__device__ __align__(1024) uint16_t g_o[S_LEN * 1024];
__device__ __align__(16) float g_kvp[16 * NH * 272];
__device__ __align__(64) float g_qn[NH * 16];
__device__ __align__(64) float g_kn[NH * 16];

struct Counters {
    int qkvB[8];
    int qkvA[8];
    int oB[16 * 8];
    int oA;
    int done;
};
__device__ Counters g_cnt;

#define STAMP(k, s) do {} while (0)
#define DSTAMP(i) do {} while (0)

__device__ __forceinline__ uint32_t smem_u32(const void* p) { return (uint32_t)__cvta_generic_to_shared(p); }
__device__ __forceinline__ void wg_fence() { asm volatile("wgmma.fence.sync.aligned;" ::: "memory"); }
__device__ __forceinline__ void wg_commit() { asm volatile("wgmma.commit_group.sync.aligned;" ::: "memory"); }
template <int N> __device__ __forceinline__ void wg_wait() { asm volatile("wgmma.wait_group.sync.aligned %0;" ::"n"(N) : "memory"); }
__device__ __forceinline__ void mbar_init(uint32_t bar, uint32_t cnt) { asm volatile("mbarrier.init.shared::cta.b64 [%0], %1;" ::"r"(bar), "r"(cnt)); }
__device__ __forceinline__ void mbar_expect_tx(uint32_t bar, uint32_t bytes) {
    asm volatile("mbarrier.arrive.expect_tx.shared::cta.b64 _, [%0], %1;" ::"r"(bar), "r"(bytes) : "memory");
}
__device__ __forceinline__ void mbar_wait(uint32_t bar, uint32_t parity) {
    asm volatile(
        "{.reg .pred p;\n"
        "WAIT_LOOP:\n"
        "mbarrier.try_wait.parity.shared::cta.b64 p, [%0], %1;\n"
        "@p bra WAIT_DONE;\n"
        "bra WAIT_LOOP;\n"
        "WAIT_DONE:\n}" ::"r"(bar), "r"(parity) : "memory");
}
__device__ __forceinline__ void mbar_arrive(uint32_t bar) { asm volatile("mbarrier.arrive.shared::cta.b64 _, [%0];" ::"r"(bar) : "memory"); }
__device__ __forceinline__ void fence_mbar_init() { asm volatile("fence.mbarrier_init.release.cluster;" ::: "memory"); }
__device__ __forceinline__ void fence_async_smem() { asm volatile("fence.proxy.async.shared::cta;" ::: "memory"); }
__device__ __forceinline__ void spin_ge(const int* p, int target) {
    int it = 0;
    while (true) {
        int v;
        asm volatile("ld.acquire.gpu.global.s32 %0, [%1];" : "=r"(v) : "l"(p) : "memory");
        if (v >= target) break;
        if (++it > (1 << 22)) __trap();
        __nanosleep(100);
    }
}
__device__ __forceinline__ void finish_ticket() {
    if (atomicAdd(&g_cnt.done, 1) == (int)gridDim.x - 1) {
        int* c = (int*)&g_cnt;
        for (int i = 0; i < (int)(sizeof(Counters) / sizeof(int)); i++) c[i] = 0;
    }
}
__device__ __forceinline__ void signal_add(int* p) { asm volatile("red.release.gpu.global.add.s32 [%0], 1;" ::"l"(p) : "memory"); }
__device__ __forceinline__ void fence_async_all() { asm volatile("fence.proxy.async.global;" ::: "memory"); }
__device__ __forceinline__ void named_bar(int id, int n) { asm volatile("bar.sync %0, %1;" ::"r"(id), "r"(n) : "memory"); }

__device__ __forceinline__ void bulk_g2s(uint32_t dst, const void* src, uint32_t bytes, uint32_t bar) {
    asm volatile("cp.async.bulk.shared::cluster.global.mbarrier::complete_tx::bytes [%0], [%1], %2, [%3];" ::"r"(dst), "l"(src), "r"(bytes), "r"(bar) : "memory");
}
__device__ __forceinline__ void bulk_s2g(void* dst, uint32_t src, uint32_t bytes) {
    asm volatile("cp.async.bulk.global.shared::cta.bulk_group [%0], [%1], %2;" ::"l"(dst), "r"(src), "r"(bytes) : "memory");
}
__device__ __forceinline__ void bulk_commit() { asm volatile("cp.async.bulk.commit_group;" ::: "memory"); }
__device__ __forceinline__ void bulk_wait0() { asm volatile("cp.async.bulk.wait_group 0;" ::: "memory"); }
__device__ __forceinline__ void tma_load_2d(uint32_t dst, const CUtensorMap* tm, int c0, int c1, uint32_t bar) {
    asm volatile("cp.async.bulk.tensor.2d.shared::cluster.global.mbarrier::complete_tx::bytes [%0], [%1, {%3, %4}], [%2];" ::"r"(dst), "l"(tm), "r"(bar), "r"(c0), "r"(c1) : "memory");
}
__device__ __forceinline__ void tma_store_2d(const CUtensorMap* tm, uint32_t src, int c0, int c1) {
    asm volatile("cp.async.bulk.tensor.2d.global.shared::cta.bulk_group [%0, {%2, %3}], [%1];" ::"l"(tm), "r"(src), "r"(c0), "r"(c1) : "memory");
}
__device__ __forceinline__ void l2_prefetch(const void* p, uint32_t bytes) {
    asm volatile("cp.async.bulk.prefetch.L2.global [%0], %1;" ::"l"(p), "r"(bytes) : "memory");
}
__device__ __forceinline__ void tma_prefetch_desc(const CUtensorMap* tm) { asm volatile("prefetch.tensormap [%0];" ::"l"(tm) : "memory"); }

__device__ __forceinline__ uint32_t pack_bf16(float lo, float hi) {
    uint32_t r; asm("cvt.rn.bf16x2.f32 %0, %1, %2;" : "=r"(r) : "f"(hi), "f"(lo)); return r;
}
__device__ __forceinline__ float ex2f(float x) { float r; asm("ex2.approx.ftz.f32 %0, %1;" : "=f"(r) : "f"(x)); return r; }
__device__ __forceinline__ float bf_lo(uint32_t p) { return __uint_as_float(p << 16); }
__device__ __forceinline__ float bf_hi(uint32_t p) { return __uint_as_float(p & 0xFFFF0000u); }
__device__ __forceinline__ void stsm_x4(uint32_t addr, uint32_t r0, uint32_t r1, uint32_t r2, uint32_t r3) {
    asm volatile("stmatrix.sync.aligned.m8n8.x4.shared.b16 [%0], {%1,%2,%3,%4};" ::"r"(addr), "r"(r0), "r"(r1), "r"(r2), "r"(r3) : "memory");
}
__device__ __forceinline__ void ldsm_x4(uint32_t addr, uint32_t* r) {
    asm volatile("ldmatrix.sync.aligned.m8n8.x4.shared.b16 {%0,%1,%2,%3}, [%4];" : "=r"(r[0]), "=r"(r[1]), "=r"(r[2]), "=r"(r[3]) : "r"(addr) : "memory");
}
__device__ __forceinline__ void ldsm_x4_t(uint32_t addr, uint32_t* r) {
    asm volatile("ldmatrix.sync.aligned.m8n8.x4.trans.shared.b16 {%0,%1,%2,%3}, [%4];" : "=r"(r[0]), "=r"(r[1]), "=r"(r[2]), "=r"(r[3]) : "r"(addr) : "memory");
}
__device__ __forceinline__ void mma_bf16(float* d, const uint32_t* a, uint32_t b0, uint32_t b1) {
    asm volatile("mma.sync.aligned.m16n8k16.row.col.f32.bf16.bf16.f32 {%0,%1,%2,%3}, {%4,%5,%6,%7}, {%8,%9}, {%0,%1,%2,%3};"
                 : "+f"(d[0]), "+f"(d[1]), "+f"(d[2]), "+f"(d[3]) : "r"(a[0]), "r"(a[1]), "r"(a[2]), "r"(a[3]), "r"(b0), "r"(b1));
}
__device__ __forceinline__ uint32_t phi_bf16x2(uint32_t p) {
    const float t0 = bf_lo(p), t1 = bf_hi(p);
    const float a0 = fmaf(t0 + fabsf(t0), 0.5f, ex2f((t0 - fabsf(t0)) * 0.7213475204444817f));
    const float a1 = fmaf(t1 + fabsf(t1), 0.5f, ex2f((t1 - fabsf(t1)) * 0.7213475204444817f));
    const uint32_t a = pack_bf16(a0, a1);
    uint32_t r;
    asm("add.rn.bf16x2 %0, %1, %2;" : "=r"(r) : "r"(a), "r"(0x35863586u));
    return r;
}
__device__ __forceinline__ float rcp_fast(float x) { float r; asm("rcp.approx.ftz.f32 %0, %1;" : "=f"(r) : "f"(x)); return r; }
template <typename T, int N> __device__ __forceinline__ void fence_regs(T (&r)[N]) {
#pragma unroll
    for (int i = 0; i < N; i++) {
        if constexpr (sizeof(T) == 4 && T(0.5) != T(0)) asm volatile("" : "+f"(r[i])::"memory");
        else asm volatile("" : "+r"(r[i])::"memory");
    }
}

__device__ __forceinline__ void wgmma_ss_n192_tb(float* d, uint64_t da, uint64_t db, int sd) {
  asm volatile("{.reg .pred p; setp.ne.b32 p, %98, 0; wgmma.mma_async.sync.aligned.m64n192k16.f32.bf16.bf16 {%0,%1,%2,%3,%4,%5,%6,%7,%8,%9,%10,%11,%12,%13,%14,%15,%16,%17,%18,%19,%20,%21,%22,%23,%24,%25,%26,%27,%28,%29,%30,%31,%32,%33,%34,%35,%36,%37,%38,%39,%40,%41,%42,%43,%44,%45,%46,%47,%48,%49,%50,%51,%52,%53,%54,%55,%56,%57,%58,%59,%60,%61,%62,%63,%64,%65,%66,%67,%68,%69,%70,%71,%72,%73,%74,%75,%76,%77,%78,%79,%80,%81,%82,%83,%84,%85,%86,%87,%88,%89,%90,%91,%92,%93,%94,%95}, %96, %97, p, 1, 1, 0, 1;}"
    : "+f"(d[0]), "+f"(d[1]), "+f"(d[2]), "+f"(d[3]), "+f"(d[4]), "+f"(d[5]), "+f"(d[6]), "+f"(d[7]), "+f"(d[8]), "+f"(d[9]), "+f"(d[10]), "+f"(d[11]), "+f"(d[12]), "+f"(d[13]), "+f"(d[14]), "+f"(d[15]), "+f"(d[16]), "+f"(d[17]), "+f"(d[18]), "+f"(d[19]), "+f"(d[20]), "+f"(d[21]), "+f"(d[22]), "+f"(d[23]), "+f"(d[24]), "+f"(d[25]), "+f"(d[26]), "+f"(d[27]), "+f"(d[28]), "+f"(d[29]), "+f"(d[30]), "+f"(d[31]), "+f"(d[32]), "+f"(d[33]), "+f"(d[34]), "+f"(d[35]), "+f"(d[36]), "+f"(d[37]), "+f"(d[38]), "+f"(d[39]), "+f"(d[40]), "+f"(d[41]), "+f"(d[42]), "+f"(d[43]), "+f"(d[44]), "+f"(d[45]), "+f"(d[46]), "+f"(d[47]), "+f"(d[48]), "+f"(d[49]), "+f"(d[50]), "+f"(d[51]), "+f"(d[52]), "+f"(d[53]), "+f"(d[54]), "+f"(d[55]), "+f"(d[56]), "+f"(d[57]), "+f"(d[58]), "+f"(d[59]), "+f"(d[60]), "+f"(d[61]), "+f"(d[62]), "+f"(d[63]), "+f"(d[64]), "+f"(d[65]), "+f"(d[66]), "+f"(d[67]), "+f"(d[68]), "+f"(d[69]), "+f"(d[70]), "+f"(d[71]), "+f"(d[72]), "+f"(d[73]), "+f"(d[74]), "+f"(d[75]), "+f"(d[76]), "+f"(d[77]), "+f"(d[78]), "+f"(d[79]), "+f"(d[80]), "+f"(d[81]), "+f"(d[82]), "+f"(d[83]), "+f"(d[84]), "+f"(d[85]), "+f"(d[86]), "+f"(d[87]), "+f"(d[88]), "+f"(d[89]), "+f"(d[90]), "+f"(d[91]), "+f"(d[92]), "+f"(d[93]), "+f"(d[94]), "+f"(d[95]) : "l"(da), "l"(db), "r"(sd));
}
__device__ __forceinline__ void wgmma_ss_n128_tb(float* d, uint64_t da, uint64_t db, int sd) {
  asm volatile("{.reg .pred p; setp.ne.b32 p, %66, 0; wgmma.mma_async.sync.aligned.m64n128k16.f32.bf16.bf16 {%0,%1,%2,%3,%4,%5,%6,%7,%8,%9,%10,%11,%12,%13,%14,%15,%16,%17,%18,%19,%20,%21,%22,%23,%24,%25,%26,%27,%28,%29,%30,%31,%32,%33,%34,%35,%36,%37,%38,%39,%40,%41,%42,%43,%44,%45,%46,%47,%48,%49,%50,%51,%52,%53,%54,%55,%56,%57,%58,%59,%60,%61,%62,%63}, %64, %65, p, 1, 1, 0, 1;}"
    : "+f"(d[0]), "+f"(d[1]), "+f"(d[2]), "+f"(d[3]), "+f"(d[4]), "+f"(d[5]), "+f"(d[6]), "+f"(d[7]), "+f"(d[8]), "+f"(d[9]), "+f"(d[10]), "+f"(d[11]), "+f"(d[12]), "+f"(d[13]), "+f"(d[14]), "+f"(d[15]), "+f"(d[16]), "+f"(d[17]), "+f"(d[18]), "+f"(d[19]), "+f"(d[20]), "+f"(d[21]), "+f"(d[22]), "+f"(d[23]), "+f"(d[24]), "+f"(d[25]), "+f"(d[26]), "+f"(d[27]), "+f"(d[28]), "+f"(d[29]), "+f"(d[30]), "+f"(d[31]), "+f"(d[32]), "+f"(d[33]), "+f"(d[34]), "+f"(d[35]), "+f"(d[36]), "+f"(d[37]), "+f"(d[38]), "+f"(d[39]), "+f"(d[40]), "+f"(d[41]), "+f"(d[42]), "+f"(d[43]), "+f"(d[44]), "+f"(d[45]), "+f"(d[46]), "+f"(d[47]), "+f"(d[48]), "+f"(d[49]), "+f"(d[50]), "+f"(d[51]), "+f"(d[52]), "+f"(d[53]), "+f"(d[54]), "+f"(d[55]), "+f"(d[56]), "+f"(d[57]), "+f"(d[58]), "+f"(d[59]), "+f"(d[60]), "+f"(d[61]), "+f"(d[62]), "+f"(d[63]) : "l"(da), "l"(db), "r"(sd));
}
template<int SD> __device__ __forceinline__ void wgmma_rs_n64(float* d, const uint32_t* a, uint64_t db) {
  asm volatile("{.reg .pred p; setp.ne.b32 p, %37, 0; wgmma.mma_async.sync.aligned.m64n64k16.f32.bf16.bf16 {%0,%1,%2,%3,%4,%5,%6,%7,%8,%9,%10,%11,%12,%13,%14,%15,%16,%17,%18,%19,%20,%21,%22,%23,%24,%25,%26,%27,%28,%29,%30,%31}, {%32,%33,%34,%35}, %36, p, 1, 1, 0;}"
    : "+f"(d[0]), "+f"(d[1]), "+f"(d[2]), "+f"(d[3]), "+f"(d[4]), "+f"(d[5]), "+f"(d[6]), "+f"(d[7]), "+f"(d[8]), "+f"(d[9]), "+f"(d[10]), "+f"(d[11]), "+f"(d[12]), "+f"(d[13]), "+f"(d[14]), "+f"(d[15]), "+f"(d[16]), "+f"(d[17]), "+f"(d[18]), "+f"(d[19]), "+f"(d[20]), "+f"(d[21]), "+f"(d[22]), "+f"(d[23]), "+f"(d[24]), "+f"(d[25]), "+f"(d[26]), "+f"(d[27]), "+f"(d[28]), "+f"(d[29]), "+f"(d[30]), "+f"(d[31]) : "r"(a[0]), "r"(a[1]), "r"(a[2]), "r"(a[3]), "l"(db), "n"(SD));
}
template<int SD> __device__ __forceinline__ void wgmma_rs_n24(float* d, const uint32_t* a, uint64_t db) {
  asm volatile("{.reg .pred p; setp.ne.b32 p, %17, 0; wgmma.mma_async.sync.aligned.m64n24k16.f32.bf16.bf16 {%0,%1,%2,%3,%4,%5,%6,%7,%8,%9,%10,%11}, {%12,%13,%14,%15}, %16, p, 1, 1, 0;}"
    : "+f"(d[0]), "+f"(d[1]), "+f"(d[2]), "+f"(d[3]), "+f"(d[4]), "+f"(d[5]), "+f"(d[6]), "+f"(d[7]), "+f"(d[8]), "+f"(d[9]), "+f"(d[10]), "+f"(d[11]) : "r"(a[0]), "r"(a[1]), "r"(a[2]), "r"(a[3]), "l"(db), "n"(SD));
}
template<int SD> __device__ __forceinline__ void wgmma_rs_n32(float* d, const uint32_t* a, uint64_t db) {
  asm volatile("{.reg .pred p; setp.ne.b32 p, %21, 0; wgmma.mma_async.sync.aligned.m64n32k16.f32.bf16.bf16 {%0,%1,%2,%3,%4,%5,%6,%7,%8,%9,%10,%11,%12,%13,%14,%15}, {%16,%17,%18,%19}, %20, p, 1, 1, 0;}"
    : "+f"(d[0]), "+f"(d[1]), "+f"(d[2]), "+f"(d[3]), "+f"(d[4]), "+f"(d[5]), "+f"(d[6]), "+f"(d[7]), "+f"(d[8]), "+f"(d[9]), "+f"(d[10]), "+f"(d[11]), "+f"(d[12]), "+f"(d[13]), "+f"(d[14]), "+f"(d[15]) : "r"(a[0]), "r"(a[1]), "r"(a[2]), "r"(a[3]), "l"(db), "n"(SD));
}
template<int SD> __device__ __forceinline__ void wgmma_rs_n40(float* d, const uint32_t* a, uint64_t db) {
  asm volatile("{.reg .pred p; setp.ne.b32 p, %25, 0; wgmma.mma_async.sync.aligned.m64n40k16.f32.bf16.bf16 {%0,%1,%2,%3,%4,%5,%6,%7,%8,%9,%10,%11,%12,%13,%14,%15,%16,%17,%18,%19}, {%20,%21,%22,%23}, %24, p, 1, 1, 0;}"
    : "+f"(d[0]), "+f"(d[1]), "+f"(d[2]), "+f"(d[3]), "+f"(d[4]), "+f"(d[5]), "+f"(d[6]), "+f"(d[7]), "+f"(d[8]), "+f"(d[9]), "+f"(d[10]), "+f"(d[11]), "+f"(d[12]), "+f"(d[13]), "+f"(d[14]), "+f"(d[15]), "+f"(d[16]), "+f"(d[17]), "+f"(d[18]), "+f"(d[19]) : "r"(a[0]), "r"(a[1]), "r"(a[2]), "r"(a[3]), "l"(db), "n"(SD));
}
template<int SD> __device__ __forceinline__ void wgmma_rs_n24_tb(float* d, const uint32_t* a, uint64_t db) {
  asm volatile("{.reg .pred p; setp.ne.b32 p, %17, 0; wgmma.mma_async.sync.aligned.m64n24k16.f32.bf16.bf16 {%0,%1,%2,%3,%4,%5,%6,%7,%8,%9,%10,%11}, {%12,%13,%14,%15}, %16, p, 1, 1, 1;}"
    : "+f"(d[0]), "+f"(d[1]), "+f"(d[2]), "+f"(d[3]), "+f"(d[4]), "+f"(d[5]), "+f"(d[6]), "+f"(d[7]), "+f"(d[8]), "+f"(d[9]), "+f"(d[10]), "+f"(d[11]) : "r"(a[0]), "r"(a[1]), "r"(a[2]), "r"(a[3]), "l"(db), "n"(SD));
}
__device__ __forceinline__ void wgmma_pv4(float* d, const uint32_t* p, uint64_t d0, uint64_t d1, uint64_t d2, uint64_t d3) {
  asm volatile("{.reg .pred p; setp.ne.b32 p, 1, 0;\n"
    "wgmma.mma_async.sync.aligned.m64n24k16.f32.bf16.bf16 {%0,%1,%2,%3,%4,%5,%6,%7,%8,%9,%10,%11}, {%12,%13,%14,%15}, %28, p, 1, 1, 1;\n"
    "wgmma.mma_async.sync.aligned.m64n24k16.f32.bf16.bf16 {%0,%1,%2,%3,%4,%5,%6,%7,%8,%9,%10,%11}, {%16,%17,%18,%19}, %29, p, 1, 1, 1;\n"
    "wgmma.mma_async.sync.aligned.m64n24k16.f32.bf16.bf16 {%0,%1,%2,%3,%4,%5,%6,%7,%8,%9,%10,%11}, {%20,%21,%22,%23}, %30, p, 1, 1, 1;\n"
    "wgmma.mma_async.sync.aligned.m64n24k16.f32.bf16.bf16 {%0,%1,%2,%3,%4,%5,%6,%7,%8,%9,%10,%11}, {%24,%25,%26,%27}, %31, p, 1, 1, 1;\n"
    "}"
    : "+f"(d[0]), "+f"(d[1]), "+f"(d[2]), "+f"(d[3]), "+f"(d[4]), "+f"(d[5]), "+f"(d[6]), "+f"(d[7]), "+f"(d[8]), "+f"(d[9]), "+f"(d[10]), "+f"(d[11])
    : "r"(p[0]), "r"(p[1]), "r"(p[2]), "r"(p[3]), "r"(p[4]), "r"(p[5]), "r"(p[6]), "r"(p[7]), "r"(p[8]), "r"(p[9]), "r"(p[10]), "r"(p[11]), "r"(p[12]), "r"(p[13]), "r"(p[14]), "r"(p[15]), "l"(d0), "l"(d1), "l"(d2), "l"(d3));
}
__device__ __forceinline__ void wgmma_qk32(float* d, const uint32_t* q, const uint32_t* one, uint64_t dk, uint64_t dc) {
  asm volatile("{.reg .pred p, r; setp.ne.b32 p, 1, 0; setp.ne.b32 r, 0, 0;\n"
    "wgmma.mma_async.sync.aligned.m64n64k16.f32.bf16.bf16 {%0,%1,%2,%3,%4,%5,%6,%7,%8,%9,%10,%11,%12,%13,%14,%15,%16,%17,%18,%19,%20,%21,%22,%23,%24,%25,%26,%27,%28,%29,%30,%31}, {%32,%33,%34,%35}, %40, r, 1, 1, 0;\n"
    "wgmma.mma_async.sync.aligned.m64n32k16.f32.bf16.bf16 {%0,%1,%2,%3,%4,%5,%6,%7,%8,%9,%10,%11,%12,%13,%14,%15}, {%36,%37,%38,%39}, %41, p, 1, 1, 0;\n"
    "}"
    : "+f"(d[0]), "+f"(d[1]), "+f"(d[2]), "+f"(d[3]), "+f"(d[4]), "+f"(d[5]), "+f"(d[6]), "+f"(d[7]), "+f"(d[8]), "+f"(d[9]), "+f"(d[10]), "+f"(d[11]), "+f"(d[12]), "+f"(d[13]), "+f"(d[14]), "+f"(d[15]), "+f"(d[16]), "+f"(d[17]), "+f"(d[18]), "+f"(d[19]), "+f"(d[20]), "+f"(d[21]), "+f"(d[22]), "+f"(d[23]), "+f"(d[24]), "+f"(d[25]), "+f"(d[26]), "+f"(d[27]), "+f"(d[28]), "+f"(d[29]), "+f"(d[30]), "+f"(d[31])
    : "r"(q[0]), "r"(q[1]), "r"(q[2]), "r"(q[3]), "r"(one[0]), "r"(one[1]), "r"(one[2]), "r"(one[3]), "l"(dk), "l"(dc));
}
__device__ __forceinline__ void wgmma_qk40(float* d, const uint32_t* q, const uint32_t* one, uint64_t dk, uint64_t dc) {
  asm volatile("{.reg .pred p, r; setp.ne.b32 p, 1, 0; setp.ne.b32 r, 0, 0;\n"
    "wgmma.mma_async.sync.aligned.m64n64k16.f32.bf16.bf16 {%0,%1,%2,%3,%4,%5,%6,%7,%8,%9,%10,%11,%12,%13,%14,%15,%16,%17,%18,%19,%20,%21,%22,%23,%24,%25,%26,%27,%28,%29,%30,%31}, {%32,%33,%34,%35}, %40, r, 1, 1, 0;\n"
    "wgmma.mma_async.sync.aligned.m64n40k16.f32.bf16.bf16 {%0,%1,%2,%3,%4,%5,%6,%7,%8,%9,%10,%11,%12,%13,%14,%15,%16,%17,%18,%19}, {%36,%37,%38,%39}, %41, p, 1, 1, 0;\n"
    "}"
    : "+f"(d[0]), "+f"(d[1]), "+f"(d[2]), "+f"(d[3]), "+f"(d[4]), "+f"(d[5]), "+f"(d[6]), "+f"(d[7]), "+f"(d[8]), "+f"(d[9]), "+f"(d[10]), "+f"(d[11]), "+f"(d[12]), "+f"(d[13]), "+f"(d[14]), "+f"(d[15]), "+f"(d[16]), "+f"(d[17]), "+f"(d[18]), "+f"(d[19]), "+f"(d[20]), "+f"(d[21]), "+f"(d[22]), "+f"(d[23]), "+f"(d[24]), "+f"(d[25]), "+f"(d[26]), "+f"(d[27]), "+f"(d[28]), "+f"(d[29]), "+f"(d[30]), "+f"(d[31])
    : "r"(q[0]), "r"(q[1]), "r"(q[2]), "r"(q[3]), "r"(one[0]), "r"(one[1]), "r"(one[2]), "r"(one[3]), "l"(dk), "l"(dc));
}

constexpr uint64_t DESC_SW128 = (uint64_t)1 << 62;
constexpr uint64_t DESC_SW32 = (uint64_t)3 << 62;
__device__ __forceinline__ uint64_t mk_desc(uint64_t sw, uint32_t addr, uint32_t lbo, uint32_t sbo) {
    return sw | ((uint64_t)(sbo >> 4) << 32) | ((uint64_t)(lbo >> 4) << 16) | (uint64_t)((addr & 0x3FFFF) >> 4);
}

constexpr uint32_t SM_BASE = 1024;
constexpr uint32_t P1_STAGE = 40960;
constexpr uint32_t P1_STGA = 98304;
constexpr uint32_t P1_RED = 148480;
constexpr uint32_t AT_Q = 0, AT_K = 16384, AT_V = 81920, AT_ONES = 147456, AT_CT = 147968, AT_TAB = 163840;
constexpr uint32_t P3_O = AT_TAB;
constexpr uint32_t BAR = 229376;
constexpr uint32_t B_FULL = BAR, B_EMPTY = BAR + 32;
constexpr uint32_t B_KV = BAR + 96, B_Q = BAR + 160, B_CONS = BAR + 168, B_WFULL = BAR + 232, B_OFULL = BAR + 296, B_OEMPTY = BAR + 328;
constexpr uint32_t B_STFREE = BAR + 360;
constexpr uint32_t OFF_MAX = BAR + 416, OFF_NORM = BAR + 512;
constexpr int SMEM_BYTES = BAR + 1024;
#define PACE 60
constexpr float QSCALE = 0.25f * 1.4426950408889634f;

struct Maps { CUtensorMap xA, xB, wA, wB, o, o16, woA, woB, out; };

__device__ __forceinline__ void phase_qkv(uint8_t* smem, const Maps& mp) {
    constexpr uint32_t sb = SM_BASE;
    const int tid = threadIdx.x, warp = tid >> 5, lane = tid & 31;
    const int nt = blockIdx.x & 7, mt = blockIdx.x >> 3;
    float* sMax = (float*)(smem + OFF_MAX);
    auto produce = [&](int kb) {
        const int s = kb & 3;
        const uint32_t full = sb + B_FULL + 8 * s, st = sb + s * P1_STAGE;
        mbar_expect_tx(full, P1_STAGE);
        tma_load_2d(st, kb < 8 ? &mp.xB : &mp.xA, (kb & 7) * 64, mt * 128, full);
#pragma unroll
        for (int j = 0; j < 3; j++) tma_load_2d(st + 16384 + j * 8192, kb < 8 ? &mp.wB : &mp.wA, j * 512 + nt * 64, (kb & 7) * 64, full);
    };
    if (tid == 0) {
        tma_prefetch_desc(&mp.xB); tma_prefetch_desc(&mp.wB);
        for (int i = 0; i < 4; i++) { mbar_init(sb + B_FULL + 8 * i, 1); mbar_init(sb + B_EMPTY + 8 * i, 2); }
        fence_mbar_init();
        DSTAMP(28);
        for (int kb = 0; kb < 4; kb++) produce(kb);
        DSTAMP(29);
        tma_prefetch_desc(&mp.xA); tma_prefetch_desc(&mp.wA);
    }
    if (tid == 32) {
                for (int i = 0; i < 4; i++) mbar_init(sb + B_STFREE + 8 * i, 2);
        mbar_init(sb + B_Q, 1);
        for (int i = 0; i < 8; i++) { mbar_init(sb + B_KV + 8 * i, 1); mbar_init(sb + B_CONS + 8 * i, 4); mbar_init(sb + B_WFULL + 8 * i, 1); }
        for (int i = 0; i < 4; i++) { mbar_init(sb + B_OFULL + 8 * i, 1); mbar_init(sb + B_OEMPTY + 8 * i, 2); }
        fence_mbar_init();
    }
    if (tid >= 64 && tid < 72) sMax[tid - 64] = 0.f;
    __syncthreads();
    STAMP(0, 1);

    const int wg = __shfl_sync(0xffffffffu, warp >> 2, 0);
    const int branchB = wg < 2;
    const int wh = wg & 1;
    const int kb0 = branchB ? 0 : 8;
    float acc[96];
#pragma unroll
    for (int i = 0; i < 96; i++) acc[i] = 0.f;
    fence_regs(acc);
    if (!branchB) {
        const int w = warp & 7, j = w * 32 + lane;
        const float f = (j + 0.5f) * (1.f / 256.f);
        const uint32_t val = (uint32_t)(__float2int_rn((exp2f(f) - 1.f) * 128.f) - (j >> 1) + (63 << 7) - 0x8000);
        uint4* tb = (uint4*)(smem + AT_TAB) + w * 32 * 8 + lane;
#pragma unroll
        for (int i = 0; i < 8; i++) {
            const uint32_t v = __shfl_sync(0xffffffffu, val, i * 4 + (lane >> 3));
            tb[i * 32] = make_uint4(v, v, v, v);
            tb[2048 + i * 32] = make_uint4(v << 16, v << 16, v << 16, v << 16);
        }
        named_bar(3, 512);
    }
    const uint64_t dA0 = mk_desc(DESC_SW128, sb + wh * 8192, 16, 1024);
#pragma unroll
    for (int i = 0; i < 8; i++) {
        const int kb = kb0 + i, s = i & 3;
        mbar_wait(sb + B_FULL + 8 * s, (i >> 2) & 1);
        if (kb == 0) STAMP(0, 2);
        if ((tid & 255) == 0) DSTAMP(kb);
        const uint64_t dA = dA0 + (uint64_t)(s * (P1_STAGE >> 4)), dB = mk_desc(DESC_SW128, sb + s * P1_STAGE + 16384, 8192, 1024);
        wg_fence();
#pragma unroll
        for (int k = 0; k < 4; k++) wgmma_ss_n192_tb(acc, dA + k * 2, dB + k * 128, 1);
        wg_commit();
        if (i == 7 && branchB) asm volatile("bar.arrive 3, 512;" ::: "memory");
        if (i > 0) {
            wg_wait<1>();
            if (i >= 5 && !branchB && (tid & 127) == 0) mbar_arrive(sb + B_STFREE + 8 * (i - 5));
            if (kb + 3 < 16) {
                const uint32_t eb = sb + B_EMPTY + 8 * ((i - 1) & 3);
                if ((tid & 127) == 0) {
                    mbar_arrive(eb);
                    if (wh == 0) { mbar_wait(eb, ((i - 1) >> 2) & 1); produce(kb + 3); }
                }
                __syncwarp();
            }
        }
    }
    wg_wait<0>();
    fence_regs(acc);
    STAMP(0, 3);

    const int wq = warp & 3, g = lane >> 2, t = lane & 3;
    const int lr = (lane & 7) + ((lane >> 3) & 1) * 8;
    const int lc = lane >> 4;
    const int row0 = mt * 128;
    const int w8 = warp & 7;
    if (branchB) {
        {
            const uint32_t eb = sb + B_EMPTY + 8 * 3;
            if ((tid & 127) == 0) {
                mbar_arrive(eb);
                if (wh == 0) { mbar_wait(eb, 1); produce(11); }
            }
            __syncwarp();
        }
        const int orow = g + (t >> 1) * 8;
        const uint32_t ooff = (uint32_t)(row0 + wh * 64 + wq * 16 + orow) * 32 + (((t & 1) ^ ((orow & 7) >> 2)) << 4);
        const bool o1 = t & 1, o2 = t & 2;
        uint32_t mymax = 0;
#pragma unroll
        for (int sl = 0; sl < 12; sl++) {
            float* a = acc + sl * 8;
            if (sl < 4) {
#pragma unroll
                for (int i = 0; i < 8; i++) a[i] *= QSCALE;
            }
            if (sl < 8) {
                const float n0 = fmaf(a[0], a[0], fmaf(a[1], a[1], fmaf(a[4], a[4], a[5] * a[5])));
                const float n1 = fmaf(a[2], a[2], fmaf(a[3], a[3], fmaf(a[6], a[6], a[7] * a[7])));
                const uint32_t m = __reduce_max_sync(0xffffffffu, __float_as_uint(fmaxf(n0, n1)));
                if (lane == sl) mymax = m;
            }
            const uint32_t w0 = pack_bf16(a[0], a[1]), w2 = pack_bf16(a[2], a[3]), w1 = pack_bf16(a[4], a[5]), w3 = pack_bf16(a[6], a[7]);
            const uint32_t r0 = __shfl_xor_sync(0xffffffffu, o1 ? w0 : w1, 1), r1 = __shfl_xor_sync(0xffffffffu, o1 ? w2 : w3, 1);
            const uint32_t x0 = o1 ? r0 : w0, x1 = o1 ? w1 : r0, y0 = o1 ? r1 : w2, y1 = o1 ? w3 : r1;
            const uint32_t q0 = __shfl_xor_sync(0xffffffffu, o2 ? x0 : y0, 2), q1 = __shfl_xor_sync(0xffffffffu, o2 ? x1 : y1, 2);
            uint4 val;
            val.x = o2 ? q0 : x0; val.y = o2 ? q1 : x1; val.z = o2 ? y0 : q0; val.w = o2 ? y1 : q1;
            const int ty = sl >> 2, head = nt * 4 + (sl & 3);
            uint8_t* dst = (uint8_t*)((ty == 0 ? g_qB : (ty == 1 ? g_kB : g_vB)) + (size_t)head * S_LEN * 16);
            *(uint4*)(dst + ooff) = val;
        }
        if (lane < 8) atomicMax((unsigned int*)&sMax[lane], mymax);
        named_bar(1, 256);
        if (tid == 0) DSTAMP(16);
        if (w8 == 7 && lane >= 8 && lane < 16) { const int i = lane - 8; (i < 4 ? g_qn : g_kn)[(nt * 4 + (i & 3)) * 16 + mt] = sMax[i]; }
        named_bar(1, 256);
        const int h = blockIdx.x >> 2, qb = blockIdx.x & 3;
        if (tid == 0) signal_add(&g_cnt.qkvB[nt]);
        auto ld_k = [&](int c) {
            mbar_expect_tx(sb + B_KV + 8 * c, 16384);
            bulk_g2s(sb + AT_K + c * 8192, g_kB + ((size_t)h * S_LEN + c * 256) * 16, 8192, sb + B_KV + 8 * c);
        };
        auto ld_v = [&](int c) { bulk_g2s(sb + AT_V + c * 8192, g_vB + ((size_t)h * S_LEN + c * 256) * 16, 8192, sb + B_KV + 8 * c); };
        if (tid == 32) {
            spin_ge(&g_cnt.qkvB[h >> 2], 16);
            fence_async_all();
            mbar_wait(sb + B_STFREE, 0);
            mbar_expect_tx(sb + B_Q, 16384 + 128);
            bulk_g2s(sb + AT_Q, g_qB + ((size_t)h * S_LEN + qb * 512) * 16, 16384, sb + B_Q);
            ld_k(0);
            bulk_g2s(sb + OFF_NORM, g_qn + h * 16, 64, sb + B_Q);
            bulk_g2s(sb + OFF_NORM + 64, g_kn + h * 16, 64, sb + B_Q);
            DSTAMP(27);
            mbar_wait(sb + B_STFREE + 16, 0);
            ld_v(0); ld_k(1); ld_v(1);
        }
        __syncwarp();
        STAMP(0, 5);
        if (tid == 0) DSTAMP(19);
        __syncwarp();
        mbar_wait(sb + B_STFREE + 24, 0);
        if (tid == 0) DSTAMP(20);
        if (w8 == 3) { for (int i = lane; i < 128; i += 32) ((uint32_t*)(smem + AT_ONES))[i] = 0x3F803F80u; }
        if (w8 == 4) {
            for (int i = lane; i < 64; i += 32) {
                const int r = i >> 3, w = i & 7, chunk = (w >> 2) ^ (r >> 2);
                ((uint32_t*)(smem + AT_CT))[i] = (chunk == 0 && (w & 3) == 0) ? 0x000043A0u : 0u;
            }
        }
        if (tid == 0) DSTAMP(21);
    } else {
        if ((tid & 127) == 0) mbar_arrive(sb + B_STFREE + 8 * 3);
        if (tid == 256) DSTAMP(22);
        named_bar(2, 256);
        const uint32_t stg = sb + P1_STGA;
        const uint32_t stAddr = stg + (wh * 64 + wq * 16 + lr) * 32 + (((lc ^ ((lr & 7) >> 2))) << 4);
#pragma unroll
        for (int sl = 0; sl < 12; sl++) {
            float* a = acc + sl * 8;
            uint32_t p0 = pack_bf16(a[0], a[1]), p1 = pack_bf16(a[2], a[3]), p2 = pack_bf16(a[4], a[5]), p3 = pack_bf16(a[6], a[7]);
            if (sl >= 4 && sl < 8) { p0 = phi_bf16x2(p0); p1 = phi_bf16x2(p1); p2 = phi_bf16x2(p2); p3 = phi_bf16x2(p3); }
            stsm_x4(stAddr + sl * 4096, p0, p1, p2, p3);
        }
        named_bar(2, 256);
        if (tid == 256) DSTAMP(23);
#pragma unroll
        for (int sl = 0; sl < 4; sl++)
            *(uint4*)((uint8_t*)(g_qA + ((size_t)(nt * 4 + sl) * S_LEN + row0) * 16) + (tid - 256) * 16) = *(const uint4*)(smem + P1_STGA + sl * 4096 + (tid - 256) * 16);
        const int hh = w8 & 3;
        const uint32_t pkb = stg + (4 + hh) * 4096 + wh * 2048, vb = stg + (8 + hh) * 4096 + wh * 2048;
        float kv0[4] = {0.f, 0.f, 0.f, 0.f}, kv1[4] = {0.f, 0.f, 0.f, 0.f}, zz[4] = {0.f, 0.f, 0.f, 0.f};
        const int ar = (lane & 7) + (lane >> 4) * 8, ac = (lane >> 3) & 1;
        const int br = (lane & 7) + ((lane >> 3) & 1) * 8, bc = lane >> 4;
#pragma unroll
        for (int ks = 0; ks < 4; ks++) {
            uint32_t af[4], bf[4];
            ldsm_x4_t(pkb + (ks * 16 + ar) * 32 + ((ac ^ ((ar & 7) >> 2)) << 4), af);
            ldsm_x4_t(vb + (ks * 16 + br) * 32 + ((bc ^ ((br & 7) >> 2)) << 4), bf);
            mma_bf16(kv0, af, bf[0], bf[1]);
            mma_bf16(kv1, af, bf[2], bf[3]);
            mma_bf16(zz, af, 0x3F803F80u, 0x3F803F80u);
        }
        if (tid == 256) DSTAMP(24);
        float* rp = (float*)(smem + P1_RED) + hh * 272;
        if (wh == 1) {
            rp[g * 16 + 2 * t] = kv0[0]; rp[g * 16 + 2 * t + 1] = kv0[1];
            rp[(g + 8) * 16 + 2 * t] = kv0[2]; rp[(g + 8) * 16 + 2 * t + 1] = kv0[3];
            rp[g * 16 + 8 + 2 * t] = kv1[0]; rp[g * 16 + 8 + 2 * t + 1] = kv1[1];
            rp[(g + 8) * 16 + 8 + 2 * t] = kv1[2]; rp[(g + 8) * 16 + 8 + 2 * t + 1] = kv1[3];
            if (t == 0) { rp[256 + g] = zz[0]; rp[256 + g + 8] = zz[2]; }
        }
        named_bar(2, 256);
        if (wh == 0) {
            float* gp = g_kvp + (size_t)(mt * NH + nt * 4 + hh) * 272;
            *(float2*)(gp + g * 16 + 2 * t) = make_float2(kv0[0] + rp[g * 16 + 2 * t], kv0[1] + rp[g * 16 + 2 * t + 1]);
            *(float2*)(gp + (g + 8) * 16 + 2 * t) = make_float2(kv0[2] + rp[(g + 8) * 16 + 2 * t], kv0[3] + rp[(g + 8) * 16 + 2 * t + 1]);
            *(float2*)(gp + g * 16 + 8 + 2 * t) = make_float2(kv1[0] + rp[g * 16 + 8 + 2 * t], kv1[1] + rp[g * 16 + 8 + 2 * t + 1]);
            *(float2*)(gp + (g + 8) * 16 + 8 + 2 * t) = make_float2(kv1[2] + rp[(g + 8) * 16 + 8 + 2 * t], kv1[3] + rp[(g + 8) * 16 + 8 + 2 * t + 1]);
            if (t == 0) { gp[256 + g] = zz[0] + rp[256 + g]; gp[256 + g + 8] = zz[2] + rp[256 + g + 8]; }
        }
        STAMP(0, 6);
    }
    fence_async_smem();
}

constexpr int AT_NT = 64;
#define AT_NP_V 32
#define AT_NP2_V 40
constexpr int AT_NP = AT_NP_V, AT_NP2 = AT_NP2_V;
constexpr float AT_SAFE2 = 56.f * 56.f;

__device__ __forceinline__ uint32_t ex2_tab2(float ya, float yb, uint32_t lane4) {
    const uint32_t a = __float_as_uint(ya), b = __float_as_uint(yb);
    uint32_t aa, ab, ta, tb, L;
    asm("lop3.b32 %0, %1, 0x7F80, %2, 0xEA;" : "=r"(aa) : "r"(a), "r"(lane4));
    asm("lop3.b32 %0, %1, 0x7F80, %2, 0xEA;" : "=r"(ab) : "r"(b), "r"(lane4));
    asm volatile("ld.shared.u32 %0, [%1+%2];" : "=r"(ta) : "r"(aa), "n"(SM_BASE + AT_TAB));
    asm volatile("ld.shared.u32 %0, [%1+%2];" : "=r"(tb) : "r"(ab), "n"(SM_BASE + AT_TAB + 32768));
    asm("prmt.b32 %0, %1, %2, 0x6521;" : "=r"(L) : "r"(a), "r"(b));
    return L + ta + tb;
}
template <int NT, int NP>
__device__ __forceinline__ void att_exp(const float* s, uint32_t* p, uint32_t lane4) {
    constexpr int PP = NP / 4, TOT = NT / 4;
#pragma unroll
    for (int i = 0; i < TOT; i++) {
        const int nb = (i * PP) / TOT, na = ((i + 1) * PP) / TOT;
        if (na != nb) p[nb] = ex2_tab2(s[2 * nb], s[2 * nb + 1], lane4);
        else { const int im = PP + i - nb; p[im] = pack_bf16(ex2f(s[2 * im]), ex2f(s[2 * im + 1])); }
    }
}

__device__ __forceinline__ void mbar_arrive_elect(uint32_t bar) {
    asm volatile("{.reg .pred p;\nelect.sync _|p, 0xffffffff;\n@p mbarrier.arrive.shared::cta.b64 _, [%0];\n}" ::"r"(bar) : "memory");
}
__device__ __forceinline__ void load_wo_elect(const Maps& mp, int branchB, int nt, int c) {
    constexpr uint32_t sb = SM_BASE;
    const CUtensorMap* tm = branchB ? &mp.woB : &mp.woA;
    asm volatile(
        "{.reg .pred p;\n"
        "elect.sync _|p, 0xffffffff;\n"
        "@p mbarrier.arrive.expect_tx.shared::cta.b64 _, [%0], 16384;\n"
        "@p cp.async.bulk.tensor.2d.shared::cluster.global.mbarrier::complete_tx::bytes [%1], [%3, {%4, %6}], [%0];\n"
        "@p cp.async.bulk.tensor.2d.shared::cluster.global.mbarrier::complete_tx::bytes [%2], [%3, {%5, %6}], [%0];\n"
        "}" ::"r"(sb + B_WFULL + 8 * c), "r"(sb + AT_K + c * 8192), "r"(sb + AT_V + c * 8192), "l"(tm), "r"(nt * 128), "r"(nt * 128 + 64), "r"(c * 64)
        : "memory");
}
__device__ __forceinline__ void load_kv_elect(int h, int c) {
    constexpr uint32_t sb = SM_BASE;
    asm volatile(
        "{.reg .pred p;\n"
        "elect.sync _|p, 0xffffffff;\n"
        "@p mbarrier.arrive.expect_tx.shared::cta.b64 _, [%0], 16384;\n"
        "@p cp.async.bulk.shared::cluster.global.mbarrier::complete_tx::bytes [%1], [%3], 8192, [%0];\n"
        "@p cp.async.bulk.shared::cluster.global.mbarrier::complete_tx::bytes [%2], [%4], 8192, [%0];\n"
        "}" ::"r"(sb + B_KV + 8 * c), "r"(sb + AT_K + c * 8192), "r"(sb + AT_V + c * 8192),
        "l"(g_kB + ((size_t)h * S_LEN + c * 256) * 16), "l"(g_vB + ((size_t)h * S_LEN + c * 256) * 16) : "memory");
}
__device__ __forceinline__ void load_wo(const Maps& mp, int branchB, int nt, int c) {
    constexpr uint32_t sb = SM_BASE;
    const CUtensorMap* tm = branchB ? &mp.woB : &mp.woA;
    mbar_expect_tx(sb + B_WFULL + 8 * c, 16384);
    tma_load_2d(sb + AT_K + c * 8192, tm, nt * 128, c * 64, sb + B_WFULL + 8 * c);
    tma_load_2d(sb + AT_V + c * 8192, tm, nt * 128 + 64, c * 64, sb + B_WFULL + 8 * c);
}

__device__ __forceinline__ void phase_attn(uint8_t* smem, const Maps& mp) {
    constexpr uint32_t sb = SM_BASE;
    const int tid = threadIdx.x, warp = (tid >> 5) & 3, lane = tid & 31;
    const int wg = __shfl_sync(0xffffffffu, tid >> 7, 0);
    const int wwarp = __shfl_sync(0xffffffffu, warp, 0);
    const int h = blockIdx.x >> 2, qb = blockIdx.x & 3;
    constexpr int NCH = 8;
    constexpr uint32_t sK = sb + AT_K, sV = sb + AT_V, sQ = sb + AT_Q, sBar = sb + B_KV;

    mbar_wait(sb + B_Q, 0);
    if (wwarp == 1) load_kv_elect(h, 2 + wg);
    if (wwarp == 2 && wg < 2) load_kv_elect(h, 6 + wg);
    STAMP(1, 2);
    bool safe;
    {
        const float* nrm = (const float*)(smem + OFF_NORM);
        const float qv = lane < 4 ? nrm[qb * 4 + lane] : 0.f;
        const float kv = lane < 16 ? nrm[16 + lane] : 0.f;
        const uint32_t qm = __reduce_max_sync(0xffffffffu, __float_as_uint(qv));
        const uint32_t km = __reduce_max_sync(0xffffffffu, __float_as_uint(kv));
        safe = (__uint_as_float(qm) * __uint_as_float(km) * (16.f * 1.05f) < AT_SAFE2);
    }
    const uint64_t dK0 = mk_desc(DESC_SW32, sK, 16, 256);
    const uint64_t dC = mk_desc(DESC_SW32, sb + AT_CT, 16, 0);
    const uint64_t dV0 = mk_desc(DESC_SW32, sV, AT_ONES - AT_V, 256);
    constexpr int64_t VSTEP = 32 - (32 << 16);
    const uint32_t lane4 = lane * 4;
    const uint32_t aone[4] = {(lane & 3) == 0 ? 0x00003F80u : 0u, (lane & 3) == 0 ? 0x00003F80u : 0u, 0u, 0u};
    const int g = lane >> 2, t = lane & 3;
    constexpr int NT = AT_NT, NP = AT_NP;
    const int oBranch = blockIdx.x >> 6, oNt = blockIdx.x & 3;

    STAMP(1, 3);
#pragma unroll 1
    for (int qi = 0; qi < 2; qi++) {
        const int qt = wg * 2 + qi;
        const int row0 = qb * 512 + qt * 64 + warp * 16;
        uint32_t qa[4];
        ldsm_x4(sQ + (qt * 64 + warp * 16 + (lane & 7) + ((lane >> 3) & 1) * 8) * 32 + ((((lane >> 4) ^ ((lane & 7) >> 2))) << 4), qa);
        float o[12], s[NT / 2];
#pragma unroll
        for (int i = 0; i < 12; i++) o[i] = 0.f;
#pragma unroll
        for (int i = 0; i < NT / 2; i++) s[i] = 0.f;
        fence_regs(o); fence_regs(s);
        if (safe) {
            uint32_t pa[NT / 4], pb[NT / 4];
            auto issue_qk = [&](uint64_t dK, int np) {
                wgmma_rs_n64<0>(s, qa, dK);
                if (np == 24) wgmma_rs_n24<1>(s, aone, dC); else if (np == 32) wgmma_rs_n32<1>(s, aone, dC); else wgmma_rs_n40<1>(s, aone, dC);
            };
            mbar_wait(sBar, 0);
            wg_fence();
            issue_qk(dK0, NP);
            wg_commit();
            wg_wait<0>();
            fence_regs(s);
            att_exp<NT, NP>(s, pa, lane4);
            uint64_t dK = dK0, dV = dV0;
            auto step = [&](uint32_t (&pc)[NT / 4], uint32_t (&pn)[NT / 4], bool last, int jt) {
                wg_fence();
                if (!last) { issue_qk(dK + (uint64_t)(jt * NT * 2 + NT * 2), (jt & 1) ? NP : AT_NP2); wg_commit(); }
#pragma unroll
                for (int kk = 0; kk < NT / 16; kk++) wgmma_rs_n24_tb<1>(o, pc + kk * 4, dV + (uint64_t)((int64_t)(jt * (NT / 16) + kk) * VSTEP));
                wg_commit();
                if (!last) {
                    wg_wait<1>();
                    fence_regs(s);
                    if (jt & 1) att_exp<NT, NP>(s, pn, lane4); else att_exp<NT, AT_NP2>(s, pn, lane4);
                }
                wg_wait<0>();
                fence_regs(pc); fence_regs(o);
            };
            constexpr int TPC = 256 / NT;
#pragma unroll 1
            for (int cch = 0; cch < NCH; cch++) {
#pragma unroll
                for (int jj = 0; jj < TPC; jj += 2) {
                    step(pa, pb, false, jj);
                    if (jj + 2 == TPC) {
                        if (cch == NCH - 1) break;
                        mbar_wait(sBar + 8 * (cch + 1), 0);
                    }
                    step(pb, pa, false, jj + 1);
                    if (jj == 0 && qi == 0 && cch == 0 && wg == 2 && wwarp == 0) {
                        asm volatile("{.reg .pred p;\nelect.sync _|p, 0xffffffff;\n@p red.release.gpu.global.add.s32 [%0], 1;\n}" ::"l"(&g_cnt.qkvA[blockIdx.x & 7]) : "memory");
                    }
                }
                dK += 256 * 2; dV += (uint64_t)(16 * VSTEP);
                if (qi == 1 && wwarp == 0 && cch < NCH - 1) {
                    mbar_arrive_elect(sb + B_CONS + 8 * cch);
                    if (cch >= 1 && wg == ((cch - 1) & 3)) { mbar_wait(sb + B_CONS + 8 * (cch - 1), 0); load_wo_elect(mp, oBranch, oNt, cch - 1); }
                }
            }
            dV -= (uint64_t)(16 * VSTEP);
            step(pb, pa, true, TPC - 1);
            if (qi == 1 && wwarp == 0) {
                mbar_arrive_elect(sb + B_CONS + 8 * 7);
                if (wg == 2) { mbar_wait(sb + B_CONS + 8 * 6, 0); load_wo_elect(mp, oBranch, oNt, 6); }
                if (wg == 3) { mbar_wait(sb + B_CONS + 8 * 7, 0); load_wo_elect(mp, oBranch, oNt, 7); }
            }
        } else {
            if (qi == 0 && tid == 256) signal_add(&g_cnt.qkvA[blockIdx.x & 7]);
            float m0 = -INFINITY, m1 = -INFINITY;
            uint32_t p[NT / 4];
#pragma unroll 1
            for (int j = 0; j < S_LEN / NT; j++) {
                if ((j * NT) % 256 == 0) mbar_wait(sBar + 8 * ((j * NT) / 256), 0);
                wg_fence();
                wgmma_rs_n64<0>(s, qa, dK0 + (uint64_t)(j * NT * 2));
                wg_commit();
                wg_wait<0>();
                fence_regs(s); fence_regs(o);
                float t0 = m0, t1 = m1;
#pragma unroll
                for (int i = 0; i < NT / 2; i += 4) { t0 = fmaxf(t0, fmaxf(s[i], s[i + 1])); t1 = fmaxf(t1, fmaxf(s[i + 2], s[i + 3])); }
                t0 = fmaxf(t0, __shfl_xor_sync(0xffffffffu, t0, 1)); t0 = fmaxf(t0, __shfl_xor_sync(0xffffffffu, t0, 2));
                t1 = fmaxf(t1, __shfl_xor_sync(0xffffffffu, t1, 1)); t1 = fmaxf(t1, __shfl_xor_sync(0xffffffffu, t1, 2));
                const float r0 = ex2f(m0 - t0), r1 = ex2f(m1 - t1);
                m0 = t0; m1 = t1;
#pragma unroll
                for (int i = 0; i < 12; i += 4) { o[i] *= r0; o[i + 1] *= r0; o[i + 2] *= r1; o[i + 3] *= r1; }
#pragma unroll
                for (int i = 0; i < NT / 4; i += 2) {
                    p[i] = pack_bf16(ex2f(s[2 * i] - m0), ex2f(s[2 * i + 1] - m0));
                    p[i + 1] = pack_bf16(ex2f(s[2 * i + 2] - m1), ex2f(s[2 * i + 3] - m1));
                }
                fence_regs(o);
                wg_fence();
#pragma unroll
                for (int kk = 0; kk < NT / 16; kk++) wgmma_rs_n24_tb<1>(o, p + kk * 4, dV0 + (uint64_t)((int64_t)(j * (NT / 16) + kk) * VSTEP));
                wg_commit();
                wg_wait<0>();
                fence_regs(p);
            }
            fence_regs(o);
        }
        const float l0 = 1.f / o[8], l1 = 1.f / o[10];
        uint32_t* op0 = (uint32_t*)(g_o + (size_t)(row0 + g) * 1024 + 512 + h * 16);
        uint32_t* op1 = (uint32_t*)(g_o + (size_t)(row0 + g + 8) * 1024 + 512 + h * 16);
        op0[t] = pack_bf16(o[0] * l0, o[1] * l0);
        op0[4 + t] = pack_bf16(o[4] * l0, o[5] * l0);
        op1[t] = pack_bf16(o[2] * l1, o[3] * l1);
        op1[4 + t] = pack_bf16(o[6] * l1, o[7] * l1);
    }
    named_bar(4 + wg, 128);
    if ((tid & 127) == 0) signal_add(&g_cnt.oB[(qb * 4 + wg) * 8 + (h >> 2)]);
    STAMP(1, 4);
    __syncthreads();
    if (!safe && tid == 0) {
        for (int c = 0; c < 8; c++) load_wo(mp, oBranch, oNt, c);
    }
}

__device__ __forceinline__ void phase_out(uint8_t* smem, const Maps& mp) {
    (void)smem;
    constexpr uint32_t sb = SM_BASE;
    const int tid = threadIdx.x, warp = tid >> 5, lane = tid & 31;
    const int branchB = blockIdx.x >> 6;
    const int mt = (blockIdx.x & 63) >> 2, nt = blockIdx.x & 3;
    const int wg = __shfl_sync(0xffffffffu, warp >> 2, 0);
    if (wg == 2) {
        if (tid == 256) {
            tma_prefetch_desc(&mp.o); tma_prefetch_desc(&mp.out);
            if (!branchB) { spin_ge(&g_cnt.oA, 4); fence_async_all(); }
            for (int kb = 0; kb < 8; kb++) {
                const int s = kb & 3;
                if (branchB) { spin_ge(&g_cnt.oB[mt * 8 + kb], 4); fence_async_all(); }
                if (kb >= 4) mbar_wait(sb + B_OEMPTY + 8 * s, 0);
                mbar_expect_tx(sb + B_OFULL + 8 * s, 16384);
                tma_load_2d(sb + P3_O + s * 16384, &mp.o, branchB * 512 + kb * 64, mt * 128, sb + B_OFULL + 8 * s);
            }
            finish_ticket();
        }
        return;
    }
    if (wg == 3) return;
    float acc[64];
#pragma unroll
    for (int i = 0; i < 64; i++) acc[i] = 0.f;
    fence_regs(acc);
#pragma unroll 1
    for (int kb = 0; kb < 8; kb++) {
        const int s = kb & 3;
        mbar_wait(sb + B_WFULL + 8 * kb, 0);
        mbar_wait(sb + B_OFULL + 8 * s, kb >> 2);
        if (kb == 0) STAMP(2, 2);
        const uint64_t dA = mk_desc(DESC_SW128, sb + P3_O + s * 16384 + wg * 8192, 16, 1024);
        const uint64_t dB = mk_desc(DESC_SW128, sb + AT_K + kb * 8192, AT_V - AT_K, 1024);
        wg_fence();
#pragma unroll
        for (int k = 0; k < 4; k++) wgmma_ss_n128_tb(acc, dA + k * 2, dB + k * 128, 1);
        wg_commit();
        if (kb >= 1 && kb <= 4) {
            wg_wait<1>();
            if ((tid & 127) == 0) mbar_arrive(sb + B_OEMPTY + 8 * (kb - 1));
        }
    }
    wg_wait<0>();
    fence_regs(acc);
    STAMP(2, 3);
    const int wq = warp & 3;
    const uint32_t stg = sb + P3_O + wg * 8192;
    const int lr = wq * 16 + (lane & 7) + ((lane >> 3) & 1) * 8, lc = lane >> 4;
#pragma unroll
    for (int j = 0; j < 8; j++) {
        const float* a = acc + j * 8;
        const int chunk = (j & 3) * 2 + lc;
        stsm_x4(stg + (j >> 2) * 16384 + lr * 128 + ((chunk ^ (lr & 7)) << 4),
                pack_bf16(a[0], a[1]), pack_bf16(a[2], a[3]), pack_bf16(a[4], a[5]), pack_bf16(a[6], a[7]));
    }
    fence_async_smem();
    named_bar(4 + wg, 128);
    if ((tid & 127) < 2) {
        const int j = tid & 1;
        tma_store_2d(&mp.out, stg + j * 16384, branchB * 512 + nt * 128 + j * 64, mt * 128 + wg * 64);
        bulk_commit();
        asm volatile("cp.async.bulk.wait_group.read 0;" ::: "memory");
    }
    STAMP(2, 4);
}

__device__ __noinline__ void linattn_mid(uint8_t* smem, int cta, const CUtensorMap* tmO16) {
    constexpr uint32_t sb = SM_BASE;
    const int tid = threadIdx.x, warp = tid >> 5, lane = tid & 31;
    constexpr int NBUF = 4;
    const uint32_t sBar = sb;
    const uint32_t sQ0 = sb + 1024;
    const uint32_t sSt = sQ0 + NBUF * 32768;
    float* skv = (float*)(smem + 1024 + NBUF * 32768 + 65536);
    if (tid == 0) { for (int i = 0; i < NBUF; i++) { mbar_init(sBar + 8 * i, 1); mbar_init(sBar + 64 + 8 * i, 16); } fence_mbar_init(); }
    __syncthreads();
    if (warp == 0 && lane == 0) { spin_ge(&g_cnt.qkvA[2 * cta], 16); spin_ge(&g_cnt.qkvA[2 * cta + 1], 16); finish_ticket(); }
    __syncthreads();
    if (lane == 0) fence_async_all();
    __syncwarp();
    STAMP(1, 2);
    auto load_chunk = [&](int c, int j) {
        bulk_g2s(sQ0 + (c % NBUF) * 32768 + j * 8192, g_qA + ((size_t)(cta * 8 + (c >> 3) * 4 + j) * S_LEN + (c & 7) * 256) * 16, 8192, sBar + 8 * (c % NBUF));
    };
    if (lane == 0 && warp < NBUF) {
        mbar_expect_tx(sBar + 8 * warp, 32768);
        for (int j = 0; j < 4; j++) load_chunk(warp, j);
    }
    for (int i = tid; i < 8 * 68; i += 512) {
        const int hh = i / 68, e = i - hh * 68;
        const float* gp = g_kvp + (size_t)(cta * 8 + hh) * 272 + e * 4;
        float4 v0, v1, v2, v3, v4, v5, v6, v7;
#define LD4(m) (*(const float4*)(gp + (size_t)(m) * NH * 272))
#define ADD4(a, b) (a).x += (b).x, (a).y += (b).y, (a).z += (b).z, (a).w += (b).w
        v0 = LD4(0); v1 = LD4(1); v2 = LD4(2); v3 = LD4(3); v4 = LD4(4); v5 = LD4(5); v6 = LD4(6); v7 = LD4(7);
        {
            const float4 w0 = LD4(8), w1 = LD4(9), w2 = LD4(10), w3 = LD4(11), w4 = LD4(12), w5 = LD4(13), w6 = LD4(14), w7 = LD4(15);
            ADD4(v0, w0); ADD4(v1, w1); ADD4(v2, w2); ADD4(v3, w3); ADD4(v4, w4); ADD4(v5, w5); ADD4(v6, w6); ADD4(v7, w7);
        }
        ADD4(v0, v4); ADD4(v1, v5); ADD4(v2, v6); ADD4(v3, v7); ADD4(v0, v2); ADD4(v1, v3); ADD4(v0, v1);
#undef LD4
#undef ADD4
        *(float4*)(skv + i * 4) = v0;
    }
    __syncthreads();
    STAMP(1, 3);
    const int g = lane >> 2, t = lane & 3;
    const int lr = (lane & 7) + ((lane >> 3) & 1) * 8, lc = lane >> 4;
    const uint32_t loff = (warp * 16 + lr) * 32 + ((lc ^ ((lr & 7) >> 2)) << 4);
#pragma unroll 1
    for (int quad = 0; quad < 2; quad++) {
        uint32_t bf[4][6];
#pragma unroll
        for (int j = 0; j < 4; j++) {
            const float* kv = skv + (quad * 4 + j) * 272;
            bf[j][0] = pack_bf16(kv[(2 * t) * 16 + g], kv[(2 * t + 1) * 16 + g]);
            bf[j][1] = pack_bf16(kv[(2 * t + 8) * 16 + g], kv[(2 * t + 9) * 16 + g]);
            bf[j][2] = pack_bf16(kv[(2 * t) * 16 + 8 + g], kv[(2 * t + 1) * 16 + 8 + g]);
            bf[j][3] = pack_bf16(kv[(2 * t + 8) * 16 + 8 + g], kv[(2 * t + 9) * 16 + 8 + g]);
            bf[j][4] = pack_bf16(kv[256 + 2 * t], kv[256 + 2 * t + 1]);
            bf[j][5] = pack_bf16(kv[256 + 2 * t + 8], kv[256 + 2 * t + 9]);
        }
#pragma unroll 1
        for (int rc = 0; rc < 8; rc++) {
            const int c = quad * 8 + rc;
            mbar_wait(sBar + 8 * (c % NBUF), (c / NBUF) & 1);
            const uint32_t qb = sQ0 + (c % NBUF) * 32768 + loff;
            const uint32_t stg = sSt + (c & 1) * 32768 + warp * 2048;
            uint32_t a[4][4];
#pragma unroll
            for (int j = 0; j < 4; j++) ldsm_x4(qb + j * 8192, a[j]);
            __syncwarp();
            if (lane == 0) {
                mbar_arrive(sBar + 64 + 8 * (c % NBUF));
                if (c >= 1 && warp == (c & 15) && c - 1 + NBUF < 16) {
                    const int cp = c - 1;
                    mbar_wait(sBar + 64 + 8 * (cp % NBUF), (cp / NBUF) & 1);
                    mbar_expect_tx(sBar + 8 * (cp % NBUF), 32768);
                    for (int j = 0; j < 4; j++) load_chunk(cp + NBUF, j);
                }
                if (c >= 2) asm volatile("cp.async.bulk.wait_group.read 1;" ::: "memory");
            }
            __syncwarp();
#pragma unroll
            for (int j = 0; j < 4; j++) {
#pragma unroll
                for (int i = 0; i < 4; i++) a[j][i] = phi_bf16x2(a[j][i]);
                float n0[4] = {0.f, 0.f, 0.f, 0.f}, n1[4] = {0.f, 0.f, 0.f, 0.f}, dn[4] = {0.f, 0.f, 0.f, 0.f};
                mma_bf16(n0, a[j], bf[j][0], bf[j][1]);
                mma_bf16(n1, a[j], bf[j][2], bf[j][3]);
                mma_bf16(dn, a[j], bf[j][4], bf[j][5]);
                const float i0 = rcp_fast(dn[0] + 1e-6f), i1 = rcp_fast(dn[2] + 1e-6f);
                stsm_x4(stg + lr * 128 + (((j * 2 + lc) ^ (lr & 7)) << 4),
                        pack_bf16(n0[0] * i0, n0[1] * i0), pack_bf16(n0[2] * i1, n0[3] * i1),
                        pack_bf16(n1[0] * i0, n1[1] * i0), pack_bf16(n1[2] * i1, n1[3] * i1));
            }
            fence_async_smem();
            __syncwarp();
            if (lane == 0) {
                tma_store_2d(tmO16, stg, cta * 128 + quad * 64, rc * 256 + warp * 16);
                bulk_commit();
            }
        }
    }
    if (lane == 0) { bulk_wait0(); fence_async_all(); }
    __syncthreads();
    if (tid == 0) signal_add(&g_cnt.oA);
    STAMP(1, 5);
}

__global__ void __launch_bounds__(512, 1) fused_kernel(const __grid_constant__ Maps mp) {
    extern __shared__ __align__(1024) uint8_t smem[];
    if (smem_u32(smem) != SM_BASE) __trap();
    STAMP(0, 0);
    if (blockIdx.x >= 128) {
        linattn_mid(smem, blockIdx.x - 128, &mp.o16);
    } else {
        phase_qkv(smem, mp);
        __syncthreads();
        STAMP(1, 1);
        phase_attn(smem, mp);
        phase_out(smem, mp);
    }
}

typedef CUresult (*EncodeFn)(CUtensorMap*, CUtensorMapDataType, cuuint32_t, void*, const cuuint64_t*, const cuuint64_t*,
                             const cuuint32_t*, const cuuint32_t*, CUtensorMapInterleave, CUtensorMapSwizzle,
                             CUtensorMapL2promotion, CUtensorMapFloatOOBfill);

void make_map(EncodeFn enc, CUtensorMap* tm, const void* ptr, uint64_t cols, uint64_t rows, uint32_t boxc, uint32_t boxr) {
    cuuint64_t dims[2] = {cols, rows};
    cuuint64_t strides[1] = {cols * 2};
    cuuint32_t box[2] = {boxc, boxr};
    cuuint32_t es[2] = {1, 1};
    enc(tm, CU_TENSOR_MAP_DATA_TYPE_BFLOAT16, 2, const_cast<void*>(ptr), dims, strides, box, es, CU_TENSOR_MAP_INTERLEAVE_NONE,
        CU_TENSOR_MAP_SWIZZLE_128B, CU_TENSOR_MAP_L2_PROMOTION_L2_256B, CU_TENSOR_MAP_FLOAT_OOB_FILL_NONE);
}

struct HostState {
    bool init;
    const void* key[7];
    Maps mp;
};
HostState g_hs;

}

extern "C" void kernel_launch(void* const* d_in, const int* in_sizes, int n_in, void* d_out, int out_size) {
    (void)in_sizes; (void)n_in; (void)out_size;
    HostState& hs = g_hs;
    bool same = hs.init && hs.key[6] == d_out;
    for (int i = 0; i < 6 && same; i++) same = hs.key[i] == d_in[i];
    if (!same) {
        void* fn = nullptr;
        cudaDriverEntryPointQueryResult qr;
        cudaGetDriverEntryPoint("cuTensorMapEncodeTiled", &fn, cudaEnableDefault, &qr);
        EncodeFn enc = (EncodeFn)fn;
        void* po = nullptr;
        cudaGetSymbolAddress(&po, g_o);
        make_map(enc, &hs.mp.xA, d_in[0], 512, 2048, 64, 128);
        make_map(enc, &hs.mp.wA, d_in[1], 1536, 512, 64, 64);
        make_map(enc, &hs.mp.woA, d_in[2], 512, 512, 64, 64);
        make_map(enc, &hs.mp.xB, d_in[3], 512, 2048, 64, 128);
        make_map(enc, &hs.mp.wB, d_in[4], 1536, 512, 64, 64);
        make_map(enc, &hs.mp.woB, d_in[5], 512, 512, 64, 64);
        make_map(enc, &hs.mp.o, po, 1024, 2048, 64, 128);
        make_map(enc, &hs.mp.o16, po, 1024, 2048, 64, 16);
        make_map(enc, &hs.mp.out, d_out, 1024, 2048, 64, 64);
        cudaFuncSetAttribute(fused_kernel, cudaFuncAttributeMaxDynamicSharedMemorySize, SMEM_BYTES);
        for (int i = 0; i < 6; i++) hs.key[i] = d_in[i];
        hs.key[6] = d_out;
        hs.init = true;
    }
    fused_kernel<<<132, 512, SMEM_BYTES, cudaStreamPerThread>>>(hs.mp);
}
```

```cpp
#include <cuda_runtime.h>
#include <cuda_bf16.h>
#include <cuda.h>
#include <stdint.h>

namespace {

constexpr int S_LEN = 2048;
constexpr int NH = 32;

__device__ __align__(1024) uint16_t g_qB[NH * S_LEN * 16];
__device__ __align__(1024) uint16_t g_kB[NH * S_LEN * 16];
__device__ __align__(1024) uint16_t g_vB[NH * S_LEN * 16];
__device__ __align__(1024) uint16_t g_qA[NH * S_LEN * 16];
__device__ __align__(1024) uint16_t g_o[S_LEN * 1024];
__device__ __align__(16) float g_kvp[16 * NH * 272];
__device__ __align__(64) float g_qn[NH * 16];
__device__ __align__(64) float g_kn[NH * 16];

struct Counters {
    int qkvB[8];
    int qkvA[8];
    int oB[16 * 8];
    int oA;
    int done;
};
__device__ Counters g_cnt;

#define STAMP(k, s) do {} while (0)
#define DSTAMP(i) do {} while (0)

__device__ __forceinline__ uint32_t smem_u32(const void* p) { return (uint32_t)__cvta_generic_to_shared(p); }
__device__ __forceinline__ void wg_fence() { asm volatile("wgmma.fence.sync.aligned;" ::: "memory"); }
__device__ __forceinline__ void wg_commit() { asm volatile("wgmma.commit_group.sync.aligned;" ::: "memory"); }
template <int N> __device__ __forceinline__ void wg_wait() { asm volatile("wgmma.wait_group.sync.aligned %0;" ::"n"(N) : "memory"); }
__device__ __forceinline__ void mbar_init(uint32_t bar, uint32_t cnt) { asm volatile("mbarrier.init.shared::cta.b64 [%0], %1;" ::"r"(bar), "r"(cnt)); }
__device__ __forceinline__ void mbar_expect_tx(uint32_t bar, uint32_t bytes) {
    asm volatile("mbarrier.arrive.expect_tx.shared::cta.b64 _, [%0], %1;" ::"r"(bar), "r"(bytes) : "memory");
}
__device__ __forceinline__ void mbar_wait(uint32_t bar, uint32_t parity) {
    asm volatile(
        "{.reg .pred p;\n"
        "WAIT_LOOP:\n"
        "mbarrier.try_wait.parity.shared::cta.b64 p, [%0], %1;\n"
        "@p bra WAIT_DONE;\n"
        "bra WAIT_LOOP;\n"
        "WAIT_DONE:\n}" ::"r"(bar), "r"(parity) : "memory");
}
__device__ __forceinline__ void mbar_arrive(uint32_t bar) { asm volatile("mbarrier.arrive.shared::cta.b64 _, [%0];" ::"r"(bar) : "memory"); }
__device__ __forceinline__ void fence_mbar_init() { asm volatile("fence.mbarrier_init.release.cluster;" ::: "memory"); }
__device__ __forceinline__ void fence_async_smem() { asm volatile("fence.proxy.async.shared::cta;" ::: "memory"); }
#define SPIN_NS 100
__device__ __forceinline__ void spin_ge(const int* p, int target) {
    int it = 0;
    while (true) {
        int v;
        asm volatile("ld.acquire.gpu.global.s32 %0, [%1];" : "=r"(v) : "l"(p) : "memory");
        if (v >= target) break;
        if (++it > (1 << 22)) __trap();
        __nanosleep(SPIN_NS);
    }
}
__device__ __forceinline__ void finish_ticket() {
    if (atomicAdd(&g_cnt.done, 1) == (int)gridDim.x - 1) {
        int* c = (int*)&g_cnt;
        for (int i = 0; i < (int)(sizeof(Counters) / sizeof(int)); i++) c[i] = 0;
    }
}
__device__ __forceinline__ void signal_add(int* p) { asm volatile("red.release.gpu.global.add.s32 [%0], 1;" ::"l"(p) : "memory"); }
__device__ __forceinline__ void fence_async_all() { asm volatile("fence.proxy.async.global;" ::: "memory"); }
__device__ __forceinline__ void named_bar(int id, int n) { asm volatile("bar.sync %0, %1;" ::"r"(id), "r"(n) : "memory"); }

__device__ __forceinline__ void bulk_g2s(uint32_t dst, const void* src, uint32_t bytes, uint32_t bar) {
    asm volatile("cp.async.bulk.shared::cluster.global.mbarrier::complete_tx::bytes [%0], [%1], %2, [%3];" ::"r"(dst), "l"(src), "r"(bytes), "r"(bar) : "memory");
}
__device__ __forceinline__ void bulk_commit() { asm volatile("cp.async.bulk.commit_group;" ::: "memory"); }
__device__ __forceinline__ void bulk_wait0() { asm volatile("cp.async.bulk.wait_group 0;" ::: "memory"); }
__device__ __forceinline__ void tma_load_2d(uint32_t dst, const CUtensorMap* tm, int c0, int c1, uint32_t bar) {
    asm volatile("cp.async.bulk.tensor.2d.shared::cluster.global.mbarrier::complete_tx::bytes [%0], [%1, {%3, %4}], [%2];" ::"r"(dst), "l"(tm), "r"(bar), "r"(c0), "r"(c1) : "memory");
}
__device__ __forceinline__ void tma_store_2d(const CUtensorMap* tm, uint32_t src, int c0, int c1) {
    asm volatile("cp.async.bulk.tensor.2d.global.shared::cta.bulk_group [%0, {%2, %3}], [%1];" ::"l"(tm), "r"(src), "r"(c0), "r"(c1) : "memory");
}
__device__ __forceinline__ void tma_prefetch_desc(const CUtensorMap* tm) { asm volatile("prefetch.tensormap [%0];" ::"l"(tm) : "memory"); }

__device__ __forceinline__ uint32_t pack_bf16(float lo, float hi) {
    uint32_t r; asm("cvt.rn.bf16x2.f32 %0, %1, %2;" : "=r"(r) : "f"(hi), "f"(lo)); return r;
}
__device__ __forceinline__ float ex2f(float x) { float r; asm("ex2.approx.ftz.f32 %0, %1;" : "=f"(r) : "f"(x)); return r; }
__device__ __forceinline__ float bf_lo(uint32_t p) { return __uint_as_float(p << 16); }
__device__ __forceinline__ float bf_hi(uint32_t p) { return __uint_as_float(p & 0xFFFF0000u); }
__device__ __forceinline__ void stsm_x4(uint32_t addr, uint32_t r0, uint32_t r1, uint32_t r2, uint32_t r3) {
    asm volatile("stmatrix.sync.aligned.m8n8.x4.shared.b16 [%0], {%1,%2,%3,%4};" ::"r"(addr), "r"(r0), "r"(r1), "r"(r2), "r"(r3) : "memory");
}
__device__ __forceinline__ void ldsm_x4(uint32_t addr, uint32_t* r) {
    asm volatile("ldmatrix.sync.aligned.m8n8.x4.shared.b16 {%0,%1,%2,%3}, [%4];" : "=r"(r[0]), "=r"(r[1]), "=r"(r[2]), "=r"(r[3]) : "r"(addr) : "memory");
}
__device__ __forceinline__ void ldsm_x4_t(uint32_t addr, uint32_t* r) {
    asm volatile("ldmatrix.sync.aligned.m8n8.x4.trans.shared.b16 {%0,%1,%2,%3}, [%4];" : "=r"(r[0]), "=r"(r[1]), "=r"(r[2]), "=r"(r[3]) : "r"(addr) : "memory");
}
__device__ __forceinline__ void mma_bf16(float* d, const uint32_t* a, uint32_t b0, uint32_t b1) {
    asm volatile("mma.sync.aligned.m16n8k16.row.col.f32.bf16.bf16.f32 {%0,%1,%2,%3}, {%4,%5,%6,%7}, {%8,%9}, {%0,%1,%2,%3};"
                 : "+f"(d[0]), "+f"(d[1]), "+f"(d[2]), "+f"(d[3]) : "r"(a[0]), "r"(a[1]), "r"(a[2]), "r"(a[3]), "r"(b0), "r"(b1));
}
__device__ __forceinline__ uint32_t phi_bf16x2(uint32_t p) {
    const float t0 = bf_lo(p), t1 = bf_hi(p);
    const float a0 = fmaf(t0 + fabsf(t0), 0.5f, ex2f((t0 - fabsf(t0)) * 0.7213475204444817f));
    const float a1 = fmaf(t1 + fabsf(t1), 0.5f, ex2f((t1 - fabsf(t1)) * 0.7213475204444817f));
    const uint32_t a = pack_bf16(a0, a1);
    uint32_t r;
    asm("add.rn.bf16x2 %0, %1, %2;" : "=r"(r) : "r"(a), "r"(0x35863586u));
    return r;
}
__device__ __forceinline__ float rcp_fast(float x) { float r; asm("rcp.approx.ftz.f32 %0, %1;" : "=f"(r) : "f"(x)); return r; }
template <typename T, int N> __device__ __forceinline__ void fence_regs(T (&r)[N]) {
#pragma unroll
    for (int i = 0; i < N; i++) {
        if constexpr (sizeof(T) == 4 && T(0.5) != T(0)) asm volatile("" : "+f"(r[i])::"memory");
        else asm volatile("" : "+r"(r[i])::"memory");
    }
}

__device__ __forceinline__ void wgmma_ss_n192_tb(float* d, uint64_t da, uint64_t db, int sd) {
  asm volatile("{.reg .pred p; setp.ne.b32 p, %98, 0; wgmma.mma_async.sync.aligned.m64n192k16.f32.bf16.bf16 {%0,%1,%2,%3,%4,%5,%6,%7,%8,%9,%10,%11,%12,%13,%14,%15,%16,%17,%18,%19,%20,%21,%22,%23,%24,%25,%26,%27,%28,%29,%30,%31,%32,%33,%34,%35,%36,%37,%38,%39,%40,%41,%42,%43,%44,%45,%46,%47,%48,%49,%50,%51,%52,%53,%54,%55,%56,%57,%58,%59,%60,%61,%62,%63,%64,%65,%66,%67,%68,%69,%70,%71,%72,%73,%74,%75,%76,%77,%78,%79,%80,%81,%82,%83,%84,%85,%86,%87,%88,%89,%90,%91,%92,%93,%94,%95}, %96, %97, p, 1, 1, 0, 1;}"
    : "+f"(d[0]), "+f"(d[1]), "+f"(d[2]), "+f"(d[3]), "+f"(d[4]), "+f"(d[5]), "+f"(d[6]), "+f"(d[7]), "+f"(d[8]), "+f"(d[9]), "+f"(d[10]), "+f"(d[11]), "+f"(d[12]), "+f"(d[13]), "+f"(d[14]), "+f"(d[15]), "+f"(d[16]), "+f"(d[17]), "+f"(d[18]), "+f"(d[19]), "+f"(d[20]), "+f"(d[21]), "+f"(d[22]), "+f"(d[23]), "+f"(d[24]), "+f"(d[25]), "+f"(d[26]), "+f"(d[27]), "+f"(d[28]), "+f"(d[29]), "+f"(d[30]), "+f"(d[31]), "+f"(d[32]), "+f"(d[33]), "+f"(d[34]), "+f"(d[35]), "+f"(d[36]), "+f"(d[37]), "+f"(d[38]), "+f"(d[39]), "+f"(d[40]), "+f"(d[41]), "+f"(d[42]), "+f"(d[43]), "+f"(d[44]), "+f"(d[45]), "+f"(d[46]), "+f"(d[47]), "+f"(d[48]), "+f"(d[49]), "+f"(d[50]), "+f"(d[51]), "+f"(d[52]), "+f"(d[53]), "+f"(d[54]), "+f"(d[55]), "+f"(d[56]), "+f"(d[57]), "+f"(d[58]), "+f"(d[59]), "+f"(d[60]), "+f"(d[61]), "+f"(d[62]), "+f"(d[63]), "+f"(d[64]), "+f"(d[65]), "+f"(d[66]), "+f"(d[67]), "+f"(d[68]), "+f"(d[69]), "+f"(d[70]), "+f"(d[71]), "+f"(d[72]), "+f"(d[73]), "+f"(d[74]), "+f"(d[75]), "+f"(d[76]), "+f"(d[77]), "+f"(d[78]), "+f"(d[79]), "+f"(d[80]), "+f"(d[81]), "+f"(d[82]), "+f"(d[83]), "+f"(d[84]), "+f"(d[85]), "+f"(d[86]), "+f"(d[87]), "+f"(d[88]), "+f"(d[89]), "+f"(d[90]), "+f"(d[91]), "+f"(d[92]), "+f"(d[93]), "+f"(d[94]), "+f"(d[95]) : "l"(da), "l"(db), "r"(sd));
}
__device__ __forceinline__ void wgmma_ss_n128_tb(float* d, uint64_t da, uint64_t db, int sd) {
  asm volatile("{.reg .pred p; setp.ne.b32 p, %66, 0; wgmma.mma_async.sync.aligned.m64n128k16.f32.bf16.bf16 {%0,%1,%2,%3,%4,%5,%6,%7,%8,%9,%10,%11,%12,%13,%14,%15,%16,%17,%18,%19,%20,%21,%22,%23,%24,%25,%26,%27,%28,%29,%30,%31,%32,%33,%34,%35,%36,%37,%38,%39,%40,%41,%42,%43,%44,%45,%46,%47,%48,%49,%50,%51,%52,%53,%54,%55,%56,%57,%58,%59,%60,%61,%62,%63}, %64, %65, p, 1, 1, 0, 1;}"
    : "+f"(d[0]), "+f"(d[1]), "+f"(d[2]), "+f"(d[3]), "+f"(d[4]), "+f"(d[5]), "+f"(d[6]), "+f"(d[7]), "+f"(d[8]), "+f"(d[9]), "+f"(d[10]), "+f"(d[11]), "+f"(d[12]), "+f"(d[13]), "+f"(d[14]), "+f"(d[15]), "+f"(d[16]), "+f"(d[17]), "+f"(d[18]), "+f"(d[19]), "+f"(d[20]), "+f"(d[21]), "+f"(d[22]), "+f"(d[23]), "+f"(d[24]), "+f"(d[25]), "+f"(d[26]), "+f"(d[27]), "+f"(d[28]), "+f"(d[29]), "+f"(d[30]), "+f"(d[31]), "+f"(d[32]), "+f"(d[33]), "+f"(d[34]), "+f"(d[35]), "+f"(d[36]), "+f"(d[37]), "+f"(d[38]), "+f"(d[39]), "+f"(d[40]), "+f"(d[41]), "+f"(d[42]), "+f"(d[43]), "+f"(d[44]), "+f"(d[45]), "+f"(d[46]), "+f"(d[47]), "+f"(d[48]), "+f"(d[49]), "+f"(d[50]), "+f"(d[51]), "+f"(d[52]), "+f"(d[53]), "+f"(d[54]), "+f"(d[55]), "+f"(d[56]), "+f"(d[57]), "+f"(d[58]), "+f"(d[59]), "+f"(d[60]), "+f"(d[61]), "+f"(d[62]), "+f"(d[63]) : "l"(da), "l"(db), "r"(sd));
}
template<int SD> __device__ __forceinline__ void wgmma_rs_n64(float* d, const uint32_t* a, uint64_t db) {
  asm volatile("{.reg .pred p; setp.ne.b32 p, %37, 0; wgmma.mma_async.sync.aligned.m64n64k16.f32.bf16.bf16 {%0,%1,%2,%3,%4,%5,%6,%7,%8,%9,%10,%11,%12,%13,%14,%15,%16,%17,%18,%19,%20,%21,%22,%23,%24,%25,%26,%27,%28,%29,%30,%31}, {%32,%33,%34,%35}, %36, p, 1, 1, 0;}"
    : "+f"(d[0]), "+f"(d[1]), "+f"(d[2]), "+f"(d[3]), "+f"(d[4]), "+f"(d[5]), "+f"(d[6]), "+f"(d[7]), "+f"(d[8]), "+f"(d[9]), "+f"(d[10]), "+f"(d[11]), "+f"(d[12]), "+f"(d[13]), "+f"(d[14]), "+f"(d[15]), "+f"(d[16]), "+f"(d[17]), "+f"(d[18]), "+f"(d[19]), "+f"(d[20]), "+f"(d[21]), "+f"(d[22]), "+f"(d[23]), "+f"(d[24]), "+f"(d[25]), "+f"(d[26]), "+f"(d[27]), "+f"(d[28]), "+f"(d[29]), "+f"(d[30]), "+f"(d[31]) : "r"(a[0]), "r"(a[1]), "r"(a[2]), "r"(a[3]), "l"(db), "n"(SD));
}
template<int SD> __device__ __forceinline__ void wgmma_rs_n24(float* d, const uint32_t* a, uint64_t db) {
  asm volatile("{.reg .pred p; setp.ne.b32 p, %17, 0; wgmma.mma_async.sync.aligned.m64n24k16.f32.bf16.bf16 {%0,%1,%2,%3,%4,%5,%6,%7,%8,%9,%10,%11}, {%12,%13,%14,%15}, %16, p, 1, 1, 0;}"
    : "+f"(d[0]), "+f"(d[1]), "+f"(d[2]), "+f"(d[3]), "+f"(d[4]), "+f"(d[5]), "+f"(d[6]), "+f"(d[7]), "+f"(d[8]), "+f"(d[9]), "+f"(d[10]), "+f"(d[11]) : "r"(a[0]), "r"(a[1]), "r"(a[2]), "r"(a[3]), "l"(db), "n"(SD));
}
template<int SD> __device__ __forceinline__ void wgmma_rs_n32(float* d, const uint32_t* a, uint64_t db) {
  asm volatile("{.reg .pred p; setp.ne.b32 p, %21, 0; wgmma.mma_async.sync.aligned.m64n32k16.f32.bf16.bf16 {%0,%1,%2,%3,%4,%5,%6,%7,%8,%9,%10,%11,%12,%13,%14,%15}, {%16,%17,%18,%19}, %20, p, 1, 1, 0;}"
    : "+f"(d[0]), "+f"(d[1]), "+f"(d[2]), "+f"(d[3]), "+f"(d[4]), "+f"(d[5]), "+f"(d[6]), "+f"(d[7]), "+f"(d[8]), "+f"(d[9]), "+f"(d[10]), "+f"(d[11]), "+f"(d[12]), "+f"(d[13]), "+f"(d[14]), "+f"(d[15]) : "r"(a[0]), "r"(a[1]), "r"(a[2]), "r"(a[3]), "l"(db), "n"(SD));
}
template<int SD> __device__ __forceinline__ void wgmma_rs_n40(float* d, const uint32_t* a, uint64_t db) {
  asm volatile("{.reg .pred p; setp.ne.b32 p, %25, 0; wgmma.mma_async.sync.aligned.m64n40k16.f32.bf16.bf16 {%0,%1,%2,%3,%4,%5,%6,%7,%8,%9,%10,%11,%12,%13,%14,%15,%16,%17,%18,%19}, {%20,%21,%22,%23}, %24, p, 1, 1, 0;}"
    : "+f"(d[0]), "+f"(d[1]), "+f"(d[2]), "+f"(d[3]), "+f"(d[4]), "+f"(d[5]), "+f"(d[6]), "+f"(d[7]), "+f"(d[8]), "+f"(d[9]), "+f"(d[10]), "+f"(d[11]), "+f"(d[12]), "+f"(d[13]), "+f"(d[14]), "+f"(d[15]), "+f"(d[16]), "+f"(d[17]), "+f"(d[18]), "+f"(d[19]) : "r"(a[0]), "r"(a[1]), "r"(a[2]), "r"(a[3]), "l"(db), "n"(SD));
}
template<int SD> __device__ __forceinline__ void wgmma_rs_n24_tb(float* d, const uint32_t* a, uint64_t db) {
  asm volatile("{.reg .pred p; setp.ne.b32 p, %17, 0; wgmma.mma_async.sync.aligned.m64n24k16.f32.bf16.bf16 {%0,%1,%2,%3,%4,%5,%6,%7,%8,%9,%10,%11}, {%12,%13,%14,%15}, %16, p, 1, 1, 1;}"
    : "+f"(d[0]), "+f"(d[1]), "+f"(d[2]), "+f"(d[3]), "+f"(d[4]), "+f"(d[5]), "+f"(d[6]), "+f"(d[7]), "+f"(d[8]), "+f"(d[9]), "+f"(d[10]), "+f"(d[11]) : "r"(a[0]), "r"(a[1]), "r"(a[2]), "r"(a[3]), "l"(db), "n"(SD));
}

constexpr uint64_t DESC_SW128 = (uint64_t)1 << 62;
constexpr uint64_t DESC_SW32 = (uint64_t)3 << 62;
__device__ __forceinline__ uint64_t mk_desc(uint64_t sw, uint32_t addr, uint32_t lbo, uint32_t sbo) {
    return sw | ((uint64_t)(sbo >> 4) << 32) | ((uint64_t)(lbo >> 4) << 16) | (uint64_t)((addr & 0x3FFFF) >> 4);
}

constexpr uint32_t SM_BASE = 1024;
constexpr uint32_t P1_STAGE = 40960;
constexpr uint32_t P1_STGA = 98304;
constexpr uint32_t P1_RED = 147456;
constexpr uint32_t AT_Q = 0, AT_K = 16384, AT_V = 81920, AT_TAB = 163840, AT_ONES = 230400, AT_CT = 230912;
constexpr uint32_t P3_O = AT_TAB;
constexpr uint32_t BAR = 229376;
constexpr uint32_t B_FULL = BAR, B_EMPTY = BAR + 32;
constexpr uint32_t B_KV = BAR + 96, B_Q = BAR + 160, B_CONS = BAR + 168, B_WFULL = BAR + 232, B_OFULL = BAR + 296, B_OEMPTY = BAR + 328;
constexpr uint32_t B_STFREE = BAR + 360;
constexpr uint32_t OFF_MAX = BAR + 416, OFF_NORM = BAR + 512;
constexpr int SMEM_BYTES = BAR + 1024 + 768;
constexpr uint32_t B_TAB = BAR + 64;
constexpr float QSCALE = 0.25f * 1.4426950408889634f;

struct Maps { CUtensorMap xA, xB, wA, wB, o, o16, woA, woB, out; };

__device__ __forceinline__ void phase_qkv(uint8_t* smem, const Maps& mp) {
    constexpr uint32_t sb = SM_BASE;
    const int tid = threadIdx.x, warp = tid >> 5, lane = tid & 31;
    const int nt = blockIdx.x & 7, mt = blockIdx.x >> 3;
    float* sMax = (float*)(smem + OFF_MAX);
    auto produce = [&](int kb) {
        const int s = kb & 3;
        const uint32_t full = sb + B_FULL + 8 * s, st = sb + s * P1_STAGE;
        mbar_expect_tx(full, P1_STAGE);
        tma_load_2d(st, kb < 8 ? &mp.xB : &mp.xA, (kb & 7) * 64, mt * 128, full);
#pragma unroll
        for (int j = 0; j < 3; j++) tma_load_2d(st + 16384 + j * 8192, kb < 8 ? &mp.wB : &mp.wA, j * 512 + nt * 64, (kb & 7) * 64, full);
    };
    if (tid == 0) {
        tma_prefetch_desc(&mp.xB); tma_prefetch_desc(&mp.wB);
        for (int i = 0; i < 4; i++) { mbar_init(sb + B_FULL + 8 * i, 1); mbar_init(sb + B_EMPTY + 8 * i, 2); }
        fence_mbar_init();
        DSTAMP(28);
        for (int kb = 0; kb < 4; kb++) produce(kb);
        DSTAMP(29);
        tma_prefetch_desc(&mp.xA); tma_prefetch_desc(&mp.wA);
    }
    if (tid == 32) {
                for (int i = 0; i < 4; i++) mbar_init(sb + B_STFREE + 8 * i, 2);
        mbar_init(sb + B_Q, 1); mbar_init(sb + B_TAB, 256);
        for (int i = 0; i < 8; i++) { mbar_init(sb + B_KV + 8 * i, 1); mbar_init(sb + B_CONS + 8 * i, 4); mbar_init(sb + B_WFULL + 8 * i, 1); }
        for (int i = 0; i < 4; i++) { mbar_init(sb + B_OFULL + 8 * i, 1); mbar_init(sb + B_OEMPTY + 8 * i, 2); }
        fence_mbar_init();
    }
    if (tid >= 64 && tid < 72) sMax[tid - 64] = 0.f;
    __syncthreads();
    STAMP(0, 1);

    const int wg = __shfl_sync(0xffffffffu, warp >> 2, 0);
    const int branchB = wg < 2;
    const int wh = wg & 1;
    const int kb0 = branchB ? 0 : 8;
    float acc[96];
#pragma unroll
    for (int i = 0; i < 96; i++) acc[i] = 0.f;
    fence_regs(acc);
    if (!branchB) {
        const int w = warp & 7, j = w * 32 + lane;
        const float f = (j + 0.5f) * (1.f / 256.f);
        const uint32_t val = (uint32_t)(__float2int_rn((exp2f(f) - 1.f) * 128.f) - (j >> 1) + (63 << 7) - 0x8000);
        uint4* tb = (uint4*)(smem + AT_TAB) + w * 32 * 8 + lane;
#pragma unroll
        for (int i = 0; i < 8; i++) {
            const uint32_t v = __shfl_sync(0xffffffffu, val, i * 4 + (lane >> 3));
            tb[i * 32] = make_uint4(v, v, v, v);
            tb[2048 + i * 32] = make_uint4(v << 16, v << 16, v << 16, v << 16);
        }
        if (w == 0) { for (int i = lane; i < 128; i += 32) ((uint32_t*)(smem + AT_ONES))[i] = 0x3F803F80u; }
        if (w == 1) {
            for (int i = lane; i < 64; i += 32) {
                const int r = i >> 3, ww = i & 7, chunk = (ww >> 2) ^ (r >> 2);
                ((uint32_t*)(smem + AT_CT))[i] = (chunk == 0 && (ww & 3) == 0) ? 0x000043A0u : 0u;
            }
        }
        fence_async_smem();
        mbar_arrive(sb + B_TAB);
        named_bar(3, 512);
    }
    const uint64_t dA0 = mk_desc(DESC_SW128, sb + wh * 8192, 16, 1024);
#pragma unroll
    for (int i = 0; i < 8; i++) {
        const int kb = kb0 + i, s = i & 3;
        mbar_wait(sb + B_FULL + 8 * s, (i >> 2) & 1);
        if (kb == 0) STAMP(0, 2);
        if ((tid & 255) == 0) DSTAMP(kb);
        const uint64_t dA = dA0 + (uint64_t)(s * (P1_STAGE >> 4)), dB = mk_desc(DESC_SW128, sb + s * P1_STAGE + 16384, 8192, 1024);
        wg_fence();
#pragma unroll
        for (int k = 0; k < 4; k++) wgmma_ss_n192_tb(acc, dA + k * 2, dB + k * 128, 1);
        wg_commit();
        if (i == 7 && branchB) asm volatile("bar.arrive 3, 512;" ::: "memory");
        if (i > 0) {
            wg_wait<1>();
            if (i >= 5 && !branchB && (tid & 127) == 0) mbar_arrive(sb + B_STFREE + 8 * (i - 5));
            if (kb + 3 < 16) {
                const uint32_t eb = sb + B_EMPTY + 8 * ((i - 1) & 3);
                if ((tid & 127) == 0) {
                    mbar_arrive(eb);
                    if (wh == 0) { mbar_wait(eb, ((i - 1) >> 2) & 1); produce(kb + 3); }
                }
                __syncwarp();
            }
        }
    }
    wg_wait<0>();
    fence_regs(acc);
    STAMP(0, 3);

    const int wq = warp & 3, g = lane >> 2, t = lane & 3;
    const int lr = (lane & 7) + ((lane >> 3) & 1) * 8;
    const int lc = lane >> 4;
    const int row0 = mt * 128;
    const int w8 = warp & 7;
    if (branchB) {
        {
            const uint32_t eb = sb + B_EMPTY + 8 * 3;
            if ((tid & 127) == 0) {
                mbar_arrive(eb);
                if (wh == 0) { mbar_wait(eb, 1); produce(11); }
            }
            __syncwarp();
        }
        const int orow = g + (t >> 1) * 8;
        const uint32_t ooff = (uint32_t)(row0 + wh * 64 + wq * 16 + orow) * 32 + (((t & 1) ^ ((orow & 7) >> 2)) << 4);
        const bool o1 = t & 1, o2 = t & 2;
        uint32_t mymax = 0;
#pragma unroll
        for (int sl = 0; sl < 12; sl++) {
            float* a = acc + sl * 8;
            if (sl < 4) {
#pragma unroll
                for (int i = 0; i < 8; i++) a[i] *= QSCALE;
            }
            if (sl < 8) {
                const float n0 = fmaf(a[0], a[0], fmaf(a[1], a[1], fmaf(a[4], a[4], a[5] * a[5])));
                const float n1 = fmaf(a[2], a[2], fmaf(a[3], a[3], fmaf(a[6], a[6], a[7] * a[7])));
                const uint32_t m = __reduce_max_sync(0xffffffffu, __float_as_uint(fmaxf(n0, n1)));
                if (lane == sl) mymax = m;
            }
            const uint32_t w0 = pack_bf16(a[0], a[1]), w2 = pack_bf16(a[2], a[3]), w1 = pack_bf16(a[4], a[5]), w3 = pack_bf16(a[6], a[7]);
            const uint32_t r0 = __shfl_xor_sync(0xffffffffu, o1 ? w0 : w1, 1), r1 = __shfl_xor_sync(0xffffffffu, o1 ? w2 : w3, 1);
            const uint32_t x0 = o1 ? r0 : w0, x1 = o1 ? w1 : r0, y0 = o1 ? r1 : w2, y1 = o1 ? w3 : r1;
            const uint32_t q0 = __shfl_xor_sync(0xffffffffu, o2 ? x0 : y0, 2), q1 = __shfl_xor_sync(0xffffffffu, o2 ? x1 : y1, 2);
            uint4 val;
            val.x = o2 ? q0 : x0; val.y = o2 ? q1 : x1; val.z = o2 ? y0 : q0; val.w = o2 ? y1 : q1;
            const int ty = sl >> 2, head = nt * 4 + (sl & 3);
            uint8_t* dst = (uint8_t*)((ty == 0 ? g_qB : (ty == 1 ? g_kB : g_vB)) + (size_t)head * S_LEN * 16);
            *(uint4*)(dst + ooff) = val;
        }
        if (lane < 8) atomicMax((unsigned int*)&sMax[lane], mymax);
        named_bar(1, 256);
        if (tid == 0) DSTAMP(16);
        if (w8 == 7 && lane >= 8 && lane < 16) { const int i = lane - 8; (i < 4 ? g_qn : g_kn)[(nt * 4 + (i & 3)) * 16 + mt] = sMax[i]; }
        named_bar(1, 256);
        const int h = blockIdx.x >> 2, qb = blockIdx.x & 3;
        if (tid == 0) signal_add(&g_cnt.qkvB[nt]);
        auto ld_k = [&](int c) {
            mbar_expect_tx(sb + B_KV + 8 * c, 16384);
            bulk_g2s(sb + AT_K + c * 8192, g_kB + ((size_t)h * S_LEN + c * 256) * 16, 8192, sb + B_KV + 8 * c);
        };
        auto ld_v = [&](int c) { bulk_g2s(sb + AT_V + c * 8192, g_vB + ((size_t)h * S_LEN + c * 256) * 16, 8192, sb + B_KV + 8 * c); };
        if (tid == 32) {
            spin_ge(&g_cnt.qkvB[h >> 2], 16);
            fence_async_all();
            mbar_wait(sb + B_STFREE, 0);
            mbar_expect_tx(sb + B_Q, 16384 + 128);
            bulk_g2s(sb + AT_Q, g_qB + ((size_t)h * S_LEN + qb * 512) * 16, 16384, sb + B_Q);
            ld_k(0);
            bulk_g2s(sb + OFF_NORM, g_qn + h * 16, 64, sb + B_Q);
            bulk_g2s(sb + OFF_NORM + 64, g_kn + h * 16, 64, sb + B_Q);
            DSTAMP(27);
            mbar_wait(sb + B_STFREE + 16, 0);
            ld_v(0); ld_k(1); ld_v(1);
        }
        __syncwarp();
        STAMP(0, 5);
    } else {
        if ((tid & 127) == 0) mbar_arrive(sb + B_STFREE + 8 * 3);
        if (tid == 256) DSTAMP(22);
        named_bar(2, 256);
        const uint32_t stg = sb + P1_STGA;
        const uint32_t stAddr = stg + (wh * 64 + wq * 16 + lr) * 32 + (((lc ^ ((lr & 7) >> 2))) << 4);
#pragma unroll
        for (int sl = 0; sl < 12; sl++) {
            float* a = acc + sl * 8;
            uint32_t p0 = pack_bf16(a[0], a[1]), p1 = pack_bf16(a[2], a[3]), p2 = pack_bf16(a[4], a[5]), p3 = pack_bf16(a[6], a[7]);
            if (sl >= 4 && sl < 8) { p0 = phi_bf16x2(p0); p1 = phi_bf16x2(p1); p2 = phi_bf16x2(p2); p3 = phi_bf16x2(p3); }
            stsm_x4(stAddr + sl * 4096, p0, p1, p2, p3);
        }
        named_bar(2, 256);
        if (tid == 256) DSTAMP(23);
#pragma unroll
        for (int sl = 0; sl < 4; sl++)
            *(uint4*)((uint8_t*)(g_qA + ((size_t)(nt * 4 + sl) * S_LEN + row0) * 16) + (tid - 256) * 16) = *(const uint4*)(smem + P1_STGA + sl * 4096 + (tid - 256) * 16);
        const int hh = w8 & 3;
        const uint32_t pkb = stg + (4 + hh) * 4096 + wh * 2048, vb = stg + (8 + hh) * 4096 + wh * 2048;
        float kv0[4] = {0.f, 0.f, 0.f, 0.f}, kv1[4] = {0.f, 0.f, 0.f, 0.f}, zz[4] = {0.f, 0.f, 0.f, 0.f};
        const int ar = (lane & 7) + (lane >> 4) * 8, ac = (lane >> 3) & 1;
        const int br = (lane & 7) + ((lane >> 3) & 1) * 8, bc = lane >> 4;
#pragma unroll
        for (int ks = 0; ks < 4; ks++) {
            uint32_t af[4], bf[4];
            ldsm_x4_t(pkb + (ks * 16 + ar) * 32 + ((ac ^ ((ar & 7) >> 2)) << 4), af);
            ldsm_x4_t(vb + (ks * 16 + br) * 32 + ((bc ^ ((br & 7) >> 2)) << 4), bf);
            mma_bf16(kv0, af, bf[0], bf[1]);
            mma_bf16(kv1, af, bf[2], bf[3]);
            mma_bf16(zz, af, 0x3F803F80u, 0x3F803F80u);
        }
        if (tid == 256) DSTAMP(24);
        float* rp = (float*)(smem + P1_RED) + hh * 272;
        if (wh == 1) {
            rp[g * 16 + 2 * t] = kv0[0]; rp[g * 16 + 2 * t + 1] = kv0[1];
            rp[(g + 8) * 16 + 2 * t] = kv0[2]; rp[(g + 8) * 16 + 2 * t + 1] = kv0[3];
            rp[g * 16 + 8 + 2 * t] = kv1[0]; rp[g * 16 + 8 + 2 * t + 1] = kv1[1];
            rp[(g + 8) * 16 + 8 + 2 * t] = kv1[2]; rp[(g + 8) * 16 + 8 + 2 * t + 1] = kv1[3];
            if (t == 0) { rp[256 + g] = zz[0]; rp[256 + g + 8] = zz[2]; }
        }
        named_bar(2, 256);
        if (wh == 0) {
            float* gp = g_kvp + (size_t)(mt * NH + nt * 4 + hh) * 272;
            *(float2*)(gp + g * 16 + 2 * t) = make_float2(kv0[0] + rp[g * 16 + 2 * t], kv0[1] + rp[g * 16 + 2 * t + 1]);
            *(float2*)(gp + (g + 8) * 16 + 2 * t) = make_float2(kv0[2] + rp[(g + 8) * 16 + 2 * t], kv0[3] + rp[(g + 8) * 16 + 2 * t + 1]);
            *(float2*)(gp + g * 16 + 8 + 2 * t) = make_float2(kv1[0] + rp[g * 16 + 8 + 2 * t], kv1[1] + rp[g * 16 + 8 + 2 * t + 1]);
            *(float2*)(gp + (g + 8) * 16 + 8 + 2 * t) = make_float2(kv1[2] + rp[(g + 8) * 16 + 8 + 2 * t], kv1[3] + rp[(g + 8) * 16 + 8 + 2 * t + 1]);
            if (t == 0) { gp[256 + g] = zz[0] + rp[256 + g]; gp[256 + g + 8] = zz[2] + rp[256 + g + 8]; }
        }
        STAMP(0, 6);
    }
}

constexpr int AT_NT = 64;
#define AT_NP_V 32
#define AT_NP2_V 40
constexpr int AT_NP = AT_NP_V, AT_NP2 = AT_NP2_V;
constexpr float AT_SAFE2 = 56.f * 56.f;

__device__ __forceinline__ uint32_t ex2_tab2(float ya, float yb, uint32_t lane4) {
    const uint32_t a = __float_as_uint(ya), b = __float_as_uint(yb);
    uint32_t aa, ab, ta, tb, L;
    asm("lop3.b32 %0, %1, 0x7F80, %2, 0xEA;" : "=r"(aa) : "r"(a), "r"(lane4));
    asm("lop3.b32 %0, %1, 0x7F80, %2, 0xEA;" : "=r"(ab) : "r"(b), "r"(lane4));
    asm volatile("ld.shared.u32 %0, [%1+%2];" : "=r"(ta) : "r"(aa), "n"(SM_BASE + AT_TAB));
    asm volatile("ld.shared.u32 %0, [%1+%2];" : "=r"(tb) : "r"(ab), "n"(SM_BASE + AT_TAB + 32768));
    asm("prmt.b32 %0, %1, %2, 0x6521;" : "=r"(L) : "r"(a), "r"(b));
    return L + ta + tb;
}
template <int NT, int NP>
__device__ __forceinline__ void att_exp(const float* s, uint32_t* p, uint32_t lane4) {
    constexpr int PP = NP / 4, TOT = NT / 4;
#pragma unroll
    for (int i = 0; i < TOT; i++) {
        const int nb = (i * PP) / TOT, na = ((i + 1) * PP) / TOT;
        if (na != nb) p[nb] = ex2_tab2(s[2 * nb], s[2 * nb + 1], lane4);
        else { const int im = PP + i - nb; p[im] = pack_bf16(ex2f(s[2 * im]), ex2f(s[2 * im + 1])); }
    }
}

__device__ __forceinline__ void mbar_arrive_elect(uint32_t bar) {
    asm volatile("{.reg .pred p;\nelect.sync _|p, 0xffffffff;\n@p mbarrier.arrive.shared::cta.b64 _, [%0];\n}" ::"r"(bar) : "memory");
}
__device__ __forceinline__ void load_wo_elect(const Maps& mp, int branchB, int nt, int c) {
    constexpr uint32_t sb = SM_BASE;
    const CUtensorMap* tm = branchB ? &mp.woB : &mp.woA;
    asm volatile(
        "{.reg .pred p;\n"
        "elect.sync _|p, 0xffffffff;\n"
        "@p mbarrier.arrive.expect_tx.shared::cta.b64 _, [%0], 16384;\n"
        "@p cp.async.bulk.tensor.2d.shared::cluster.global.mbarrier::complete_tx::bytes [%1], [%3, {%4, %6}], [%0];\n"
        "@p cp.async.bulk.tensor.2d.shared::cluster.global.mbarrier::complete_tx::bytes [%2], [%3, {%5, %6}], [%0];\n"
        "}" ::"r"(sb + B_WFULL + 8 * c), "r"(sb + AT_K + c * 8192), "r"(sb + AT_V + c * 8192), "l"(tm), "r"(nt * 128), "r"(nt * 128 + 64), "r"(c * 64)
        : "memory");
}
__device__ __forceinline__ void load_kv_elect(int h, int c) {
    constexpr uint32_t sb = SM_BASE;
    asm volatile(
        "{.reg .pred p;\n"
        "elect.sync _|p, 0xffffffff;\n"
        "@p mbarrier.arrive.expect_tx.shared::cta.b64 _, [%0], 16384;\n"
        "@p cp.async.bulk.shared::cluster.global.mbarrier::complete_tx::bytes [%1], [%3], 8192, [%0];\n"
        "@p cp.async.bulk.shared::cluster.global.mbarrier::complete_tx::bytes [%2], [%4], 8192, [%0];\n"
        "}" ::"r"(sb + B_KV + 8 * c), "r"(sb + AT_K + c * 8192), "r"(sb + AT_V + c * 8192),
        "l"(g_kB + ((size_t)h * S_LEN + c * 256) * 16), "l"(g_vB + ((size_t)h * S_LEN + c * 256) * 16) : "memory");
}
__device__ __forceinline__ void load_wo(const Maps& mp, int branchB, int nt, int c) {
    constexpr uint32_t sb = SM_BASE;
    const CUtensorMap* tm = branchB ? &mp.woB : &mp.woA;
    mbar_expect_tx(sb + B_WFULL + 8 * c, 16384);
    tma_load_2d(sb + AT_K + c * 8192, tm, nt * 128, c * 64, sb + B_WFULL + 8 * c);
    tma_load_2d(sb + AT_V + c * 8192, tm, nt * 128 + 64, c * 64, sb + B_WFULL + 8 * c);
}

__device__ __forceinline__ void phase_attn(uint8_t* smem, const Maps& mp) {
    constexpr uint32_t sb = SM_BASE;
    const int tid = threadIdx.x, warp = (tid >> 5) & 3, lane = tid & 31;
    const int wg = __shfl_sync(0xffffffffu, tid >> 7, 0);
    const int wwarp = __shfl_sync(0xffffffffu, warp, 0);
    const int h = blockIdx.x >> 2, qb = blockIdx.x & 3;
    constexpr int NCH = 8;
    constexpr uint32_t sK = sb + AT_K, sV = sb + AT_V, sQ = sb + AT_Q, sBar = sb + B_KV;

    __syncwarp();
    mbar_wait(sb + B_TAB, 0);
    mbar_wait(sb + B_Q, 0);
    if (wg >= 2) {
        named_bar(2, 256);
        if (wwarp < 3) load_kv_elect(h, 2 + (wg - 2) * 3 + wwarp);
    }
    __syncwarp();
    STAMP(1, 2);
    bool safe;
    {
        const float* nrm = (const float*)(smem + OFF_NORM);
        const float qv = lane < 4 ? nrm[qb * 4 + lane] : 0.f;
        const float kv = lane < 16 ? nrm[16 + lane] : 0.f;
        const uint32_t qm = __reduce_max_sync(0xffffffffu, __float_as_uint(qv));
        const uint32_t km = __reduce_max_sync(0xffffffffu, __float_as_uint(kv));
        safe = (__uint_as_float(qm) * __uint_as_float(km) * (16.f * 1.05f) < AT_SAFE2);
    }
    const uint64_t dK0 = mk_desc(DESC_SW32, sK, 16, 256);
    const uint64_t dC = mk_desc(DESC_SW32, sb + AT_CT, 16, 0);
    const uint64_t dV0 = mk_desc(DESC_SW32, sV, AT_ONES - AT_V, 256);
    constexpr int64_t VSTEP = 32 - (32 << 16);
    const uint32_t lane4 = lane * 4;
    const uint32_t aone[4] = {(lane & 3) == 0 ? 0x00003F80u : 0u, (lane & 3) == 0 ? 0x00003F80u : 0u, 0u, 0u};
    const int g = lane >> 2, t = lane & 3;
    constexpr int NT = AT_NT, NP = AT_NP;
    const int oBranch = blockIdx.x >> 6, oNt = blockIdx.x & 3;

    STAMP(1, 3);
#pragma unroll 1
    for (int qi = 0; qi < 2; qi++) {
        const int qt = wg * 2 + qi;
        const int row0 = qb * 512 + qt * 64 + warp * 16;
        uint32_t qa[4];
        ldsm_x4(sQ + (qt * 64 + warp * 16 + (lane & 7) + ((lane >> 3) & 1) * 8) * 32 + ((((lane >> 4) ^ ((lane & 7) >> 2))) << 4), qa);
        float o[12], s[NT / 2];
#pragma unroll
        for (int i = 0; i < 12; i++) o[i] = 0.f;
#pragma unroll
        for (int i = 0; i < NT / 2; i++) s[i] = 0.f;
        fence_regs(o); fence_regs(s);
        if (safe) {
            uint32_t pa[NT / 4], pb[NT / 4];
            auto issue_qk = [&](uint64_t dK, int np) {
                wgmma_rs_n64<0>(s, qa, dK);
                if (np == 24) wgmma_rs_n24<1>(s, aone, dC); else if (np == 32) wgmma_rs_n32<1>(s, aone, dC); else wgmma_rs_n40<1>(s, aone, dC);
            };
            mbar_wait(sBar, 0);
            wg_fence();
            issue_qk(dK0, NP);
            wg_commit();
            wg_wait<0>();
            fence_regs(s);
            att_exp<NT, NP>(s, pa, lane4);
            uint64_t dK = dK0, dV = dV0;
            auto step = [&](uint32_t (&pc)[NT / 4], uint32_t (&pn)[NT / 4], bool last, int jt) {
                wg_fence();
                if (!last) { issue_qk(dK + (uint64_t)(jt * NT * 2 + NT * 2), (jt & 1) ? NP : AT_NP2); wg_commit(); }
#pragma unroll
                for (int kk = 0; kk < NT / 16; kk++) wgmma_rs_n24_tb<1>(o, pc + kk * 4, dV + (uint64_t)((int64_t)(jt * (NT / 16) + kk) * VSTEP));
                wg_commit();
                if (!last) {
                    wg_wait<1>();
                    fence_regs(s);
                    if (jt & 1) att_exp<NT, NP>(s, pn, lane4); else att_exp<NT, AT_NP2>(s, pn, lane4);
                }
                wg_wait<0>();
                fence_regs(pc); fence_regs(o);
            };
            constexpr int TPC = 256 / NT;
#pragma unroll 1
            for (int cch = 0; cch < NCH; cch++) {
                const int cu = __shfl_sync(0xffffffffu, cch, 0);
                dK = dK0 + (uint64_t)(cu * 512); dV = dV0 + (uint64_t)((int64_t)(cu * 16) * VSTEP);
                asm volatile("" : "+l"(dK), "+l"(dV));
#pragma unroll
                for (int jj = 0; jj < TPC; jj += 2) {
                    step(pa, pb, false, jj);
                    if (jj + 2 == TPC) {
                        if (cch == NCH - 1) break;
                        mbar_wait(sBar + 8 * (cch + 1), 0);
                    }
                    step(pb, pa, false, jj + 1);
                    if (jj == 0 && qi == 0 && cch == 0 && wg == 2 && wwarp == 0) {
                        asm volatile("{.reg .pred p;\nelect.sync _|p, 0xffffffff;\n@p red.release.gpu.global.add.s32 [%0], 1;\n}" ::"l"(&g_cnt.qkvA[blockIdx.x & 7]) : "memory");
                    }
                }
                if (qi == 1 && wwarp == 0 && cch < NCH - 1) {
                    mbar_arrive_elect(sb + B_CONS + 8 * cch);
                    if (cch >= 1 && wg == ((cch - 1) & 3)) { mbar_wait(sb + B_CONS + 8 * (cch - 1), 0); load_wo_elect(mp, oBranch, oNt, cch - 1); }
                }
            }
            dV = dV0 + (uint64_t)((int64_t)(7 * 16) * VSTEP);
            step(pb, pa, true, TPC - 1);
            if (qi == 1 && wwarp == 0) {
                mbar_arrive_elect(sb + B_CONS + 8 * 7);
                if (wg == 2) { mbar_wait(sb + B_CONS + 8 * 6, 0); load_wo_elect(mp, oBranch, oNt, 6); }
                if (wg == 3) { mbar_wait(sb + B_CONS + 8 * 7, 0); load_wo_elect(mp, oBranch, oNt, 7); }
            }
        } else {
            if (qi == 0 && tid == 256) signal_add(&g_cnt.qkvA[blockIdx.x & 7]);
            float m0 = -INFINITY, m1 = -INFINITY;
            uint32_t p[NT / 4];
#pragma unroll 1
            for (int j = 0; j < S_LEN / NT; j++) {
                if ((j * NT) % 256 == 0) mbar_wait(sBar + 8 * ((j * NT) / 256), 0);
                wg_fence();
                wgmma_rs_n64<0>(s, qa, dK0 + (uint64_t)(j * NT * 2));
                wg_commit();
                wg_wait<0>();
                fence_regs(s); fence_regs(o);
                float t0 = m0, t1 = m1;
#pragma unroll
                for (int i = 0; i < NT / 2; i += 4) { t0 = fmaxf(t0, fmaxf(s[i], s[i + 1])); t1 = fmaxf(t1, fmaxf(s[i + 2], s[i + 3])); }
                t0 = fmaxf(t0, __shfl_xor_sync(0xffffffffu, t0, 1)); t0 = fmaxf(t0, __shfl_xor_sync(0xffffffffu, t0, 2));
                t1 = fmaxf(t1, __shfl_xor_sync(0xffffffffu, t1, 1)); t1 = fmaxf(t1, __shfl_xor_sync(0xffffffffu, t1, 2));
                const float r0 = ex2f(m0 - t0), r1 = ex2f(m1 - t1);
                m0 = t0; m1 = t1;
#pragma unroll
                for (int i = 0; i < 12; i += 4) { o[i] *= r0; o[i + 1] *= r0; o[i + 2] *= r1; o[i + 3] *= r1; }
#pragma unroll
                for (int i = 0; i < NT / 4; i += 2) {
                    p[i] = pack_bf16(ex2f(s[2 * i] - m0), ex2f(s[2 * i + 1] - m0));
                    p[i + 1] = pack_bf16(ex2f(s[2 * i + 2] - m1), ex2f(s[2 * i + 3] - m1));
                }
                fence_regs(o);
                wg_fence();
#pragma unroll
                for (int kk = 0; kk < NT / 16; kk++) wgmma_rs_n24_tb<1>(o, p + kk * 4, dV0 + (uint64_t)((int64_t)(j * (NT / 16) + kk) * VSTEP));
                wg_commit();
                wg_wait<0>();
                fence_regs(p);
            }
            fence_regs(o);
        }
        const float l0 = 1.f / o[8], l1 = 1.f / o[10];
        uint32_t* op0 = (uint32_t*)(g_o + (size_t)(row0 + g) * 1024 + 512 + h * 16);
        uint32_t* op1 = (uint32_t*)(g_o + (size_t)(row0 + g + 8) * 1024 + 512 + h * 16);
        op0[t] = pack_bf16(o[0] * l0, o[1] * l0);
        op0[4 + t] = pack_bf16(o[4] * l0, o[5] * l0);
        op1[t] = pack_bf16(o[2] * l1, o[3] * l1);
        op1[4 + t] = pack_bf16(o[6] * l1, o[7] * l1);
    }
    named_bar(4 + wg, 128);
    if ((tid & 127) == 0) signal_add(&g_cnt.oB[(qb * 4 + wg) * 8 + (h >> 2)]);
    STAMP(1, 4);
    __syncthreads();
    if (!safe && tid == 0) {
        for (int c = 0; c < 8; c++) load_wo(mp, oBranch, oNt, c);
    }
}

__device__ __forceinline__ void phase_out(uint8_t* smem, const Maps& mp) {
    (void)smem;
    constexpr uint32_t sb = SM_BASE;
    const int tid = threadIdx.x, warp = tid >> 5, lane = tid & 31;
    const int branchB = blockIdx.x >> 6;
    const int mt = (blockIdx.x & 63) >> 2, nt = blockIdx.x & 3;
    const int wg = __shfl_sync(0xffffffffu, warp >> 2, 0);
    if (wg == 2) {
        if (tid == 256) {
            tma_prefetch_desc(&mp.o); tma_prefetch_desc(&mp.out);
            if (!branchB) { spin_ge(&g_cnt.oA, 4); fence_async_all(); }
            for (int kb = 0; kb < 8; kb++) {
                const int s = kb & 3;
                if (branchB) { spin_ge(&g_cnt.oB[mt * 8 + kb], 4); fence_async_all(); }
                if (kb >= 4) mbar_wait(sb + B_OEMPTY + 8 * s, 0);
                mbar_expect_tx(sb + B_OFULL + 8 * s, 16384);
                tma_load_2d(sb + P3_O + s * 16384, &mp.o, branchB * 512 + kb * 64, mt * 128, sb + B_OFULL + 8 * s);
            }
            finish_ticket();
        }
        return;
    }
    if (wg == 3) return;
    float acc[64];
#pragma unroll
    for (int i = 0; i < 64; i++) acc[i] = 0.f;
    fence_regs(acc);
#pragma unroll 1
    for (int kb = 0; kb < 8; kb++) {
        const int s = kb & 3;
        mbar_wait(sb + B_WFULL + 8 * kb, 0);
        mbar_wait(sb + B_OFULL + 8 * s, kb >> 2);
        if (kb == 0) STAMP(2, 2);
        const uint64_t dA = mk_desc(DESC_SW128, sb + P3_O + s * 16384 + wg * 8192, 16, 1024);
        const uint64_t dB = mk_desc(DESC_SW128, sb + AT_K + kb * 8192, AT_V - AT_K, 1024);
        wg_fence();
#pragma unroll
        for (int k = 0; k < 4; k++) wgmma_ss_n128_tb(acc, dA + k * 2, dB + k * 128, 1);
        wg_commit();
        if (kb >= 1 && kb <= 4) {
            wg_wait<1>();
            if ((tid & 127) == 0) mbar_arrive(sb + B_OEMPTY + 8 * (kb - 1));
        }
    }
    wg_wait<0>();
    fence_regs(acc);
    STAMP(2, 3);
    const int wq = warp & 3;
    const uint32_t stg = sb + P3_O + wg * 8192;
    const int lr = wq * 16 + (lane & 7) + ((lane >> 3) & 1) * 8, lc = lane >> 4;
#pragma unroll
    for (int j = 0; j < 8; j++) {
        const float* a = acc + j * 8;
        const int chunk = (j & 3) * 2 + lc;
        stsm_x4(stg + (j >> 2) * 16384 + lr * 128 + ((chunk ^ (lr & 7)) << 4),
                pack_bf16(a[0], a[1]), pack_bf16(a[2], a[3]), pack_bf16(a[4], a[5]), pack_bf16(a[6], a[7]));
    }
    fence_async_smem();
    named_bar(4 + wg, 128);
    if ((tid & 127) < 2) {
        const int j = tid & 1;
        tma_store_2d(&mp.out, stg + j * 16384, branchB * 512 + nt * 128 + j * 64, mt * 128 + wg * 64);
        bulk_commit();
        asm volatile("cp.async.bulk.wait_group.read 0;" ::: "memory");
    }
    STAMP(2, 4);
}

__device__ __noinline__ void linattn_mid(uint8_t* smem, int cta, const CUtensorMap* tmO16) {
    constexpr uint32_t sb = SM_BASE;
    const int tid = threadIdx.x, warp = tid >> 5, lane = tid & 31;
    constexpr int NBUF = 4;
    const uint32_t sBar = sb;
    const uint32_t sQ0 = sb + 1024;
    const uint32_t sSt = sQ0 + NBUF * 32768;
    float* skv = (float*)(smem + 1024 + NBUF * 32768 + 65536);
    if (tid == 0) { for (int i = 0; i < NBUF; i++) { mbar_init(sBar + 8 * i, 1); mbar_init(sBar + 64 + 8 * i, 16); } fence_mbar_init(); }
    __syncthreads();
    if (warp == 0 && lane == 0) { spin_ge(&g_cnt.qkvA[2 * cta], 16); spin_ge(&g_cnt.qkvA[2 * cta + 1], 16); finish_ticket(); }
    __syncthreads();
    if (lane == 0) fence_async_all();
    __syncwarp();
    STAMP(1, 2);
    auto load_chunk = [&](int c, int j) {
        bulk_g2s(sQ0 + (c % NBUF) * 32768 + j * 8192, g_qA + ((size_t)(cta * 8 + (c >> 3) * 4 + j) * S_LEN + (c & 7) * 256) * 16, 8192, sBar + 8 * (c % NBUF));
    };
    if (lane == 0 && warp < NBUF) {
        mbar_expect_tx(sBar + 8 * warp, 32768);
        for (int j = 0; j < 4; j++) load_chunk(warp, j);
    }
    for (int i = tid; i < 8 * 68; i += 512) {
        const int hh = i / 68, e = i - hh * 68;
        const float* gp = g_kvp + (size_t)(cta * 8 + hh) * 272 + e * 4;
        float4 v0, v1, v2, v3, v4, v5, v6, v7;
#define LD4(m) (*(const float4*)(gp + (size_t)(m) * NH * 272))
#define ADD4(a, b) (a).x += (b).x, (a).y += (b).y, (a).z += (b).z, (a).w += (b).w
        v0 = LD4(0); v1 = LD4(1); v2 = LD4(2); v3 = LD4(3); v4 = LD4(4); v5 = LD4(5); v6 = LD4(6); v7 = LD4(7);
        {
            const float4 w0 = LD4(8), w1 = LD4(9), w2 = LD4(10), w3 = LD4(11), w4 = LD4(12), w5 = LD4(13), w6 = LD4(14), w7 = LD4(15);
            ADD4(v0, w0); ADD4(v1, w1); ADD4(v2, w2); ADD4(v3, w3); ADD4(v4, w4); ADD4(v5, w5); ADD4(v6, w6); ADD4(v7, w7);
        }
        ADD4(v0, v4); ADD4(v1, v5); ADD4(v2, v6); ADD4(v3, v7); ADD4(v0, v2); ADD4(v1, v3); ADD4(v0, v1);
#undef LD4
#undef ADD4
        *(float4*)(skv + i * 4) = v0;
    }
    __syncthreads();
    STAMP(1, 3);
    const int g = lane >> 2, t = lane & 3;
    const int lr = (lane & 7) + ((lane >> 3) & 1) * 8, lc = lane >> 4;
    const uint32_t loff = (warp * 16 + lr) * 32 + ((lc ^ ((lr & 7) >> 2)) << 4);
#pragma unroll 1
    for (int quad = 0; quad < 2; quad++) {
        uint32_t bf[4][6];
#pragma unroll
        for (int j = 0; j < 4; j++) {
            const float* kv = skv + (quad * 4 + j) * 272;
            bf[j][0] = pack_bf16(kv[(2 * t) * 16 + g], kv[(2 * t + 1) * 16 + g]);
            bf[j][1] = pack_bf16(kv[(2 * t + 8) * 16 + g], kv[(2 * t + 9) * 16 + g]);
            bf[j][2] = pack_bf16(kv[(2 * t) * 16 + 8 + g], kv[(2 * t + 1) * 16 + 8 + g]);
            bf[j][3] = pack_bf16(kv[(2 * t + 8) * 16 + 8 + g], kv[(2 * t + 9) * 16 + 8 + g]);
            bf[j][4] = pack_bf16(kv[256 + 2 * t], kv[256 + 2 * t + 1]);
            bf[j][5] = pack_bf16(kv[256 + 2 * t + 8], kv[256 + 2 * t + 9]);
        }
#pragma unroll 1
        for (int rc = 0; rc < 8; rc++) {
            const int c = quad * 8 + rc;
            mbar_wait(sBar + 8 * (c % NBUF), (c / NBUF) & 1);
            const uint32_t qb = sQ0 + (c % NBUF) * 32768 + loff;
            const uint32_t stg = sSt + (c & 1) * 32768 + warp * 2048;
            uint32_t a[4][4];
#pragma unroll
            for (int j = 0; j < 4; j++) ldsm_x4(qb + j * 8192, a[j]);
            __syncwarp();
            if (lane == 0) {
                mbar_arrive(sBar + 64 + 8 * (c % NBUF));
                if (c >= 1 && warp == (c & 15) && c - 1 + NBUF < 16) {
                    const int cp = c - 1;
                    mbar_wait(sBar + 64 + 8 * (cp % NBUF), (cp / NBUF) & 1);
                    mbar_expect_tx(sBar + 8 * (cp % NBUF), 32768);
                    for (int j = 0; j < 4; j++) load_chunk(cp + NBUF, j);
                }
                if (c >= 2) asm volatile("cp.async.bulk.wait_group.read 1;" ::: "memory");
            }
            __syncwarp();
#pragma unroll
            for (int j = 0; j < 4; j++) {
#pragma unroll
                for (int i = 0; i < 4; i++) a[j][i] = phi_bf16x2(a[j][i]);
                float n0[4] = {0.f, 0.f, 0.f, 0.f}, n1[4] = {0.f, 0.f, 0.f, 0.f}, dn[4] = {0.f, 0.f, 0.f, 0.f};
                mma_bf16(n0, a[j], bf[j][0], bf[j][1]);
                mma_bf16(n1, a[j], bf[j][2], bf[j][3]);
                mma_bf16(dn, a[j], bf[j][4], bf[j][5]);
                const float i0 = rcp_fast(dn[0] + 1e-6f), i1 = rcp_fast(dn[2] + 1e-6f);
                stsm_x4(stg + lr * 128 + (((j * 2 + lc) ^ (lr & 7)) << 4),
                        pack_bf16(n0[0] * i0, n0[1] * i0), pack_bf16(n0[2] * i1, n0[3] * i1),
                        pack_bf16(n1[0] * i0, n1[1] * i0), pack_bf16(n1[2] * i1, n1[3] * i1));
            }
            fence_async_smem();
            __syncwarp();
            if (lane == 0) {
                tma_store_2d(tmO16, stg, cta * 128 + quad * 64, rc * 256 + warp * 16);
                bulk_commit();
            }
        }
    }
    if (lane == 0) { bulk_wait0(); fence_async_all(); }
    __syncthreads();
    if (tid == 0) signal_add(&g_cnt.oA);
    STAMP(1, 5);
}

__global__ void __launch_bounds__(512, 1) fused_kernel(const __grid_constant__ Maps mp) {
    extern __shared__ __align__(1024) uint8_t smem[];
    if (smem_u32(smem) != SM_BASE) __trap();
    STAMP(0, 0);
    if (blockIdx.x >= 128) {
        linattn_mid(smem, blockIdx.x - 128, &mp.o16);
    } else {
        phase_qkv(smem, mp);
        STAMP(1, 1);
        phase_attn(smem, mp);
        phase_out(smem, mp);
    }
}

typedef CUresult (*EncodeFn)(CUtensorMap*, CUtensorMapDataType, cuuint32_t, void*, const cuuint64_t*, const cuuint64_t*,
                             const cuuint32_t*, const cuuint32_t*, CUtensorMapInterleave, CUtensorMapSwizzle,
                             CUtensorMapL2promotion, CUtensorMapFloatOOBfill);

void make_map(EncodeFn enc, CUtensorMap* tm, const void* ptr, uint64_t cols, uint64_t rows, uint32_t boxc, uint32_t boxr) {
    cuuint64_t dims[2] = {cols, rows};
    cuuint64_t strides[1] = {cols * 2};
    cuuint32_t box[2] = {boxc, boxr};
    cuuint32_t es[2] = {1, 1};
    enc(tm, CU_TENSOR_MAP_DATA_TYPE_BFLOAT16, 2, const_cast<void*>(ptr), dims, strides, box, es, CU_TENSOR_MAP_INTERLEAVE_NONE,
        CU_TENSOR_MAP_SWIZZLE_128B, CU_TENSOR_MAP_L2_PROMOTION_L2_256B, CU_TENSOR_MAP_FLOAT_OOB_FILL_NONE);
}

struct HostState {
    bool init;
    const void* key[7];
    Maps mp;
};
HostState g_hs;

}

extern "C" void kernel_launch(void* const* d_in, const int* in_sizes, int n_in, void* d_out, int out_size) {
    (void)in_sizes; (void)n_in; (void)out_size;
    HostState& hs = g_hs;
    bool same = hs.init && hs.key[6] == d_out;
    for (int i = 0; i < 6 && same; i++) same = hs.key[i] == d_in[i];
    if (!same) {
        void* fn = nullptr;
        cudaDriverEntryPointQueryResult qr;
        cudaGetDriverEntryPoint("cuTensorMapEncodeTiled", &fn, cudaEnableDefault, &qr);
        EncodeFn enc = (EncodeFn)fn;
        void* po = nullptr;
        cudaGetSymbolAddress(&po, g_o);
        make_map(enc, &hs.mp.xA, d_in[0], 512, 2048, 64, 128);
        make_map(enc, &hs.mp.wA, d_in[1], 1536, 512, 64, 64);
        make_map(enc, &hs.mp.woA, d_in[2], 512, 512, 64, 64);
        make_map(enc, &hs.mp.xB, d_in[3], 512, 2048, 64, 128);
        make_map(enc, &hs.mp.wB, d_in[4], 1536, 512, 64, 64);
        make_map(enc, &hs.mp.woB, d_in[5], 512, 512, 64, 64);
        make_map(enc, &hs.mp.o, po, 1024, 2048, 64, 128);
        make_map(enc, &hs.mp.o16, po, 1024, 2048, 64, 16);
        make_map(enc, &hs.mp.out, d_out, 1024, 2048, 64, 64);
        cudaFuncSetAttribute(fused_kernel, cudaFuncAttributeMaxDynamicSharedMemorySize, SMEM_BYTES);
        for (int i = 0; i < 6; i++) hs.key[i] = d_in[i];
        hs.key[6] = d_out;
        hs.init = true;
    }
    fused_kernel<<<132, 512, SMEM_BYTES, cudaStreamPerThread>>>(hs.mp);
}
```

```cpp
#include <cuda_runtime.h>
#include <cuda_bf16.h>
#include <cuda.h>
#include <stdint.h>

namespace {

constexpr int S_LEN = 2048;
constexpr int NH = 32;

__device__ __align__(1024) uint16_t g_qB[NH * S_LEN * 16];
__device__ __align__(1024) uint16_t g_kB[NH * S_LEN * 16];
__device__ __align__(1024) uint16_t g_vB[NH * S_LEN * 16];
__device__ __align__(1024) uint16_t g_qA[NH * S_LEN * 16];
__device__ __align__(1024) uint16_t g_o[S_LEN * 1024];
__device__ __align__(16) float g_kvp[16 * NH * 272];
__device__ __align__(64) float g_qn[NH * 16];
__device__ __align__(64) float g_kn[NH * 16];

struct Counters {
    int qkvB[8];
    int qkvA[8];
    int oB[32 * 8];
    int oA;
    int done;
};
__device__ Counters g_cnt;

#define STAMP(k, s) do {} while (0)
#define DSTAMP(i) do {} while (0)

__device__ __forceinline__ uint32_t smem_u32(const void* p) { return (uint32_t)__cvta_generic_to_shared(p); }
__device__ __forceinline__ void wg_fence() { asm volatile("wgmma.fence.sync.aligned;" ::: "memory"); }
__device__ __forceinline__ void wg_commit() { asm volatile("wgmma.commit_group.sync.aligned;" ::: "memory"); }
template <int N> __device__ __forceinline__ void wg_wait() { asm volatile("wgmma.wait_group.sync.aligned %0;" ::"n"(N) : "memory"); }
__device__ __forceinline__ void mbar_init(uint32_t bar, uint32_t cnt) { asm volatile("mbarrier.init.shared::cta.b64 [%0], %1;" ::"r"(bar), "r"(cnt)); }
__device__ __forceinline__ void mbar_expect_tx(uint32_t bar, uint32_t bytes) {
    asm volatile("mbarrier.arrive.expect_tx.shared::cta.b64 _, [%0], %1;" ::"r"(bar), "r"(bytes) : "memory");
}
__device__ __forceinline__ void mbar_wait(uint32_t bar, uint32_t parity) {
    asm volatile(
        "{.reg .pred p;\n"
        "WAIT_LOOP:\n"
        "mbarrier.try_wait.parity.shared::cta.b64 p, [%0], %1;\n"
        "@p bra WAIT_DONE;\n"
        "bra WAIT_LOOP;\n"
        "WAIT_DONE:\n}" ::"r"(bar), "r"(parity) : "memory");
}
__device__ __forceinline__ void mbar_arrive(uint32_t bar) { asm volatile("mbarrier.arrive.shared::cta.b64 _, [%0];" ::"r"(bar) : "memory"); }
__device__ __forceinline__ void fence_mbar_init() { asm volatile("fence.mbarrier_init.release.cluster;" ::: "memory"); }
__device__ __forceinline__ void fence_async_smem() { asm volatile("fence.proxy.async.shared::cta;" ::: "memory"); }
#define SPIN_NS 100
__device__ __forceinline__ void spin_ge(const int* p, int target) {
    int it = 0;
    while (true) {
        int v;
        asm volatile("ld.acquire.gpu.global.s32 %0, [%1];" : "=r"(v) : "l"(p) : "memory");
        if (v >= target) break;
        if (++it > (1 << 22)) __trap();
        __nanosleep(SPIN_NS);
    }
}
__device__ __forceinline__ void finish_ticket() {
    if (atomicAdd(&g_cnt.done, 1) == (int)gridDim.x - 1) {
        int* c = (int*)&g_cnt;
        for (int i = 0; i < (int)(sizeof(Counters) / sizeof(int)); i++) c[i] = 0;
    }
}
__device__ __forceinline__ void signal_add(int* p) { asm volatile("red.release.gpu.global.add.s32 [%0], 1;" ::"l"(p) : "memory"); }
__device__ __forceinline__ void fence_async_all() { asm volatile("fence.proxy.async.global;" ::: "memory"); }
__device__ __forceinline__ void named_bar(int id, int n) { asm volatile("bar.sync %0, %1;" ::"r"(id), "r"(n) : "memory"); }

__device__ __forceinline__ void bulk_g2s(uint32_t dst, const void* src, uint32_t bytes, uint32_t bar) {
    asm volatile("cp.async.bulk.shared::cluster.global.mbarrier::complete_tx::bytes [%0], [%1], %2, [%3];" ::"r"(dst), "l"(src), "r"(bytes), "r"(bar) : "memory");
}
__device__ __forceinline__ void bulk_commit() { asm volatile("cp.async.bulk.commit_group;" ::: "memory"); }
__device__ __forceinline__ void bulk_wait0() { asm volatile("cp.async.bulk.wait_group 0;" ::: "memory"); }
__device__ __forceinline__ void tma_load_2d(uint32_t dst, const CUtensorMap* tm, int c0, int c1, uint32_t bar) {
    asm volatile("cp.async.bulk.tensor.2d.shared::cluster.global.mbarrier::complete_tx::bytes [%0], [%1, {%3, %4}], [%2];" ::"r"(dst), "l"(tm), "r"(bar), "r"(c0), "r"(c1) : "memory");
}
__device__ __forceinline__ void tma_store_2d(const CUtensorMap* tm, uint32_t src, int c0, int c1) {
    asm volatile("cp.async.bulk.tensor.2d.global.shared::cta.bulk_group [%0, {%2, %3}], [%1];" ::"l"(tm), "r"(src), "r"(c0), "r"(c1) : "memory");
}
__device__ __forceinline__ void tma_prefetch_desc(const CUtensorMap* tm) { asm volatile("prefetch.tensormap [%0];" ::"l"(tm) : "memory"); }

__device__ __forceinline__ uint32_t pack_bf16(float lo, float hi) {
    uint32_t r; asm("cvt.rn.bf16x2.f32 %0, %1, %2;" : "=r"(r) : "f"(hi), "f"(lo)); return r;
}
__device__ __forceinline__ float ex2f(float x) { float r; asm("ex2.approx.ftz.f32 %0, %1;" : "=f"(r) : "f"(x)); return r; }
__device__ __forceinline__ float bf_lo(uint32_t p) { return __uint_as_float(p << 16); }
__device__ __forceinline__ float bf_hi(uint32_t p) { return __uint_as_float(p & 0xFFFF0000u); }
__device__ __forceinline__ void stsm_x4(uint32_t addr, uint32_t r0, uint32_t r1, uint32_t r2, uint32_t r3) {
    asm volatile("stmatrix.sync.aligned.m8n8.x4.shared.b16 [%0], {%1,%2,%3,%4};" ::"r"(addr), "r"(r0), "r"(r1), "r"(r2), "r"(r3) : "memory");
}
__device__ __forceinline__ void ldsm_x4(uint32_t addr, uint32_t* r) {
    asm volatile("ldmatrix.sync.aligned.m8n8.x4.shared.b16 {%0,%1,%2,%3}, [%4];" : "=r"(r[0]), "=r"(r[1]), "=r"(r[2]), "=r"(r[3]) : "r"(addr) : "memory");
}
__device__ __forceinline__ void ldsm_x4_t(uint32_t addr, uint32_t* r) {
    asm volatile("ldmatrix.sync.aligned.m8n8.x4.trans.shared.b16 {%0,%1,%2,%3}, [%4];" : "=r"(r[0]), "=r"(r[1]), "=r"(r[2]), "=r"(r[3]) : "r"(addr) : "memory");
}
__device__ __forceinline__ void mma_bf16(float* d, const uint32_t* a, uint32_t b0, uint32_t b1) {
    asm volatile("mma.sync.aligned.m16n8k16.row.col.f32.bf16.bf16.f32 {%0,%1,%2,%3}, {%4,%5,%6,%7}, {%8,%9}, {%0,%1,%2,%3};"
                 : "+f"(d[0]), "+f"(d[1]), "+f"(d[2]), "+f"(d[3]) : "r"(a[0]), "r"(a[1]), "r"(a[2]), "r"(a[3]), "r"(b0), "r"(b1));
}
__device__ __forceinline__ uint32_t phi_bf16x2(uint32_t p) {
    const float t0 = bf_lo(p), t1 = bf_hi(p);
    const float a0 = fmaf(t0 + fabsf(t0), 0.5f, ex2f((t0 - fabsf(t0)) * 0.7213475204444817f));
    const float a1 = fmaf(t1 + fabsf(t1), 0.5f, ex2f((t1 - fabsf(t1)) * 0.7213475204444817f));
    const uint32_t a = pack_bf16(a0, a1);
    uint32_t r;
    asm("add.rn.bf16x2 %0, %1, %2;" : "=r"(r) : "r"(a), "r"(0x35863586u));
    return r;
}
__device__ __forceinline__ float rcp_fast(float x) { float r; asm("rcp.approx.ftz.f32 %0, %1;" : "=f"(r) : "f"(x)); return r; }
template <typename T, int N> __device__ __forceinline__ void fence_regs(T (&r)[N]) {
#pragma unroll
    for (int i = 0; i < N; i++) {
        if constexpr (sizeof(T) == 4 && T(0.5) != T(0)) asm volatile("" : "+f"(r[i])::"memory");
        else asm volatile("" : "+r"(r[i])::"memory");
    }
}

__device__ __forceinline__ void wgmma_ss_n192_tb(float* d, uint64_t da, uint64_t db, int sd) {
  asm volatile("{.reg .pred p; setp.ne.b32 p, %98, 0; wgmma.mma_async.sync.aligned.m64n192k16.f32.bf16.bf16 {%0,%1,%2,%3,%4,%5,%6,%7,%8,%9,%10,%11,%12,%13,%14,%15,%16,%17,%18,%19,%20,%21,%22,%23,%24,%25,%26,%27,%28,%29,%30,%31,%32,%33,%34,%35,%36,%37,%38,%39,%40,%41,%42,%43,%44,%45,%46,%47,%48,%49,%50,%51,%52,%53,%54,%55,%56,%57,%58,%59,%60,%61,%62,%63,%64,%65,%66,%67,%68,%69,%70,%71,%72,%73,%74,%75,%76,%77,%78,%79,%80,%81,%82,%83,%84,%85,%86,%87,%88,%89,%90,%91,%92,%93,%94,%95}, %96, %97, p, 1, 1, 0, 1;}"
    : "+f"(d[0]), "+f"(d[1]), "+f"(d[2]), "+f"(d[3]), "+f"(d[4]), "+f"(d[5]), "+f"(d[6]), "+f"(d[7]), "+f"(d[8]), "+f"(d[9]), "+f"(d[10]), "+f"(d[11]), "+f"(d[12]), "+f"(d[13]), "+f"(d[14]), "+f"(d[15]), "+f"(d[16]), "+f"(d[17]), "+f"(d[18]), "+f"(d[19]), "+f"(d[20]), "+f"(d[21]), "+f"(d[22]), "+f"(d[23]), "+f"(d[24]), "+f"(d[25]), "+f"(d[26]), "+f"(d[27]), "+f"(d[28]), "+f"(d[29]), "+f"(d[30]), "+f"(d[31]), "+f"(d[32]), "+f"(d[33]), "+f"(d[34]), "+f"(d[35]), "+f"(d[36]), "+f"(d[37]), "+f"(d[38]), "+f"(d[39]), "+f"(d[40]), "+f"(d[41]), "+f"(d[42]), "+f"(d[43]), "+f"(d[44]), "+f"(d[45]), "+f"(d[46]), "+f"(d[47]), "+f"(d[48]), "+f"(d[49]), "+f"(d[50]), "+f"(d[51]), "+f"(d[52]), "+f"(d[53]), "+f"(d[54]), "+f"(d[55]), "+f"(d[56]), "+f"(d[57]), "+f"(d[58]), "+f"(d[59]), "+f"(d[60]), "+f"(d[61]), "+f"(d[62]), "+f"(d[63]), "+f"(d[64]), "+f"(d[65]), "+f"(d[66]), "+f"(d[67]), "+f"(d[68]), "+f"(d[69]), "+f"(d[70]), "+f"(d[71]), "+f"(d[72]), "+f"(d[73]), "+f"(d[74]), "+f"(d[75]), "+f"(d[76]), "+f"(d[77]), "+f"(d[78]), "+f"(d[79]), "+f"(d[80]), "+f"(d[81]), "+f"(d[82]), "+f"(d[83]), "+f"(d[84]), "+f"(d[85]), "+f"(d[86]), "+f"(d[87]), "+f"(d[88]), "+f"(d[89]), "+f"(d[90]), "+f"(d[91]), "+f"(d[92]), "+f"(d[93]), "+f"(d[94]), "+f"(d[95]) : "l"(da), "l"(db), "r"(sd));
}
__device__ __forceinline__ void wgmma_ss_n128_tb(float* d, uint64_t da, uint64_t db, int sd) {
  asm volatile("{.reg .pred p; setp.ne.b32 p, %66, 0; wgmma.mma_async.sync.aligned.m64n128k16.f32.bf16.bf16 {%0,%1,%2,%3,%4,%5,%6,%7,%8,%9,%10,%11,%12,%13,%14,%15,%16,%17,%18,%19,%20,%21,%22,%23,%24,%25,%26,%27,%28,%29,%30,%31,%32,%33,%34,%35,%36,%37,%38,%39,%40,%41,%42,%43,%44,%45,%46,%47,%48,%49,%50,%51,%52,%53,%54,%55,%56,%57,%58,%59,%60,%61,%62,%63}, %64, %65, p, 1, 1, 0, 1;}"
    : "+f"(d[0]), "+f"(d[1]), "+f"(d[2]), "+f"(d[3]), "+f"(d[4]), "+f"(d[5]), "+f"(d[6]), "+f"(d[7]), "+f"(d[8]), "+f"(d[9]), "+f"(d[10]), "+f"(d[11]), "+f"(d[12]), "+f"(d[13]), "+f"(d[14]), "+f"(d[15]), "+f"(d[16]), "+f"(d[17]), "+f"(d[18]), "+f"(d[19]), "+f"(d[20]), "+f"(d[21]), "+f"(d[22]), "+f"(d[23]), "+f"(d[24]), "+f"(d[25]), "+f"(d[26]), "+f"(d[27]), "+f"(d[28]), "+f"(d[29]), "+f"(d[30]), "+f"(d[31]), "+f"(d[32]), "+f"(d[33]), "+f"(d[34]), "+f"(d[35]), "+f"(d[36]), "+f"(d[37]), "+f"(d[38]), "+f"(d[39]), "+f"(d[40]), "+f"(d[41]), "+f"(d[42]), "+f"(d[43]), "+f"(d[44]), "+f"(d[45]), "+f"(d[46]), "+f"(d[47]), "+f"(d[48]), "+f"(d[49]), "+f"(d[50]), "+f"(d[51]), "+f"(d[52]), "+f"(d[53]), "+f"(d[54]), "+f"(d[55]), "+f"(d[56]), "+f"(d[57]), "+f"(d[58]), "+f"(d[59]), "+f"(d[60]), "+f"(d[61]), "+f"(d[62]), "+f"(d[63]) : "l"(da), "l"(db), "r"(sd));
}
template<int SD> __device__ __forceinline__ void wgmma_rs_n64(float* d, const uint32_t* a, uint64_t db) {
  asm volatile("{.reg .pred p; setp.ne.b32 p, %37, 0; wgmma.mma_async.sync.aligned.m64n64k16.f32.bf16.bf16 {%0,%1,%2,%3,%4,%5,%6,%7,%8,%9,%10,%11,%12,%13,%14,%15,%16,%17,%18,%19,%20,%21,%22,%23,%24,%25,%26,%27,%28,%29,%30,%31}, {%32,%33,%34,%35}, %36, p, 1, 1, 0;}"
    : "+f"(d[0]), "+f"(d[1]), "+f"(d[2]), "+f"(d[3]), "+f"(d[4]), "+f"(d[5]), "+f"(d[6]), "+f"(d[7]), "+f"(d[8]), "+f"(d[9]), "+f"(d[10]), "+f"(d[11]), "+f"(d[12]), "+f"(d[13]), "+f"(d[14]), "+f"(d[15]), "+f"(d[16]), "+f"(d[17]), "+f"(d[18]), "+f"(d[19]), "+f"(d[20]), "+f"(d[21]), "+f"(d[22]), "+f"(d[23]), "+f"(d[24]), "+f"(d[25]), "+f"(d[26]), "+f"(d[27]), "+f"(d[28]), "+f"(d[29]), "+f"(d[30]), "+f"(d[31]) : "r"(a[0]), "r"(a[1]), "r"(a[2]), "r"(a[3]), "l"(db), "n"(SD));
}
template<int SD> __device__ __forceinline__ void wgmma_rs_n24(float* d, const uint32_t* a, uint64_t db) {
  asm volatile("{.reg .pred p; setp.ne.b32 p, %17, 0; wgmma.mma_async.sync.aligned.m64n24k16.f32.bf16.bf16 {%0,%1,%2,%3,%4,%5,%6,%7,%8,%9,%10,%11}, {%12,%13,%14,%15}, %16, p, 1, 1, 0;}"
    : "+f"(d[0]), "+f"(d[1]), "+f"(d[2]), "+f"(d[3]), "+f"(d[4]), "+f"(d[5]), "+f"(d[6]), "+f"(d[7]), "+f"(d[8]), "+f"(d[9]), "+f"(d[10]), "+f"(d[11]) : "r"(a[0]), "r"(a[1]), "r"(a[2]), "r"(a[3]), "l"(db), "n"(SD));
}
template<int SD> __device__ __forceinline__ void wgmma_rs_n32(float* d, const uint32_t* a, uint64_t db) {
  asm volatile("{.reg .pred p; setp.ne.b32 p, %21, 0; wgmma.mma_async.sync.aligned.m64n32k16.f32.bf16.bf16 {%0,%1,%2,%3,%4,%5,%6,%7,%8,%9,%10,%11,%12,%13,%14,%15}, {%16,%17,%18,%19}, %20, p, 1, 1, 0;}"
    : "+f"(d[0]), "+f"(d[1]), "+f"(d[2]), "+f"(d[3]), "+f"(d[4]), "+f"(d[5]), "+f"(d[6]), "+f"(d[7]), "+f"(d[8]), "+f"(d[9]), "+f"(d[10]), "+f"(d[11]), "+f"(d[12]), "+f"(d[13]), "+f"(d[14]), "+f"(d[15]) : "r"(a[0]), "r"(a[1]), "r"(a[2]), "r"(a[3]), "l"(db), "n"(SD));
}
template<int SD> __device__ __forceinline__ void wgmma_rs_n40(float* d, const uint32_t* a, uint64_t db) {
  asm volatile("{.reg .pred p; setp.ne.b32 p, %25, 0; wgmma.mma_async.sync.aligned.m64n40k16.f32.bf16.bf16 {%0,%1,%2,%3,%4,%5,%6,%7,%8,%9,%10,%11,%12,%13,%14,%15,%16,%17,%18,%19}, {%20,%21,%22,%23}, %24, p, 1, 1, 0;}"
    : "+f"(d[0]), "+f"(d[1]), "+f"(d[2]), "+f"(d[3]), "+f"(d[4]), "+f"(d[5]), "+f"(d[6]), "+f"(d[7]), "+f"(d[8]), "+f"(d[9]), "+f"(d[10]), "+f"(d[11]), "+f"(d[12]), "+f"(d[13]), "+f"(d[14]), "+f"(d[15]), "+f"(d[16]), "+f"(d[17]), "+f"(d[18]), "+f"(d[19]) : "r"(a[0]), "r"(a[1]), "r"(a[2]), "r"(a[3]), "l"(db), "n"(SD));
}
template<int SD> __device__ __forceinline__ void wgmma_rs_n24_tb(float* d, const uint32_t* a, uint64_t db) {
  asm volatile("{.reg .pred p; setp.ne.b32 p, %17, 0; wgmma.mma_async.sync.aligned.m64n24k16.f32.bf16.bf16 {%0,%1,%2,%3,%4,%5,%6,%7,%8,%9,%10,%11}, {%12,%13,%14,%15}, %16, p, 1, 1, 1;}"
    : "+f"(d[0]), "+f"(d[1]), "+f"(d[2]), "+f"(d[3]), "+f"(d[4]), "+f"(d[5]), "+f"(d[6]), "+f"(d[7]), "+f"(d[8]), "+f"(d[9]), "+f"(d[10]), "+f"(d[11]) : "r"(a[0]), "r"(a[1]), "r"(a[2]), "r"(a[3]), "l"(db), "n"(SD));
}

constexpr uint64_t DESC_SW128 = (uint64_t)1 << 62;
constexpr uint64_t DESC_SW32 = (uint64_t)3 << 62;
__device__ __forceinline__ uint64_t mk_desc(uint64_t sw, uint32_t addr, uint32_t lbo, uint32_t sbo) {
    return sw | ((uint64_t)(sbo >> 4) << 32) | ((uint64_t)(lbo >> 4) << 16) | (uint64_t)((addr & 0x3FFFF) >> 4);
}

constexpr uint32_t SM_BASE = 1024;
constexpr uint32_t P1_STAGE = 40960;
constexpr uint32_t P1_STGA = 98304;
constexpr uint32_t P1_RED = 147456;
constexpr uint32_t AT_Q = 0, AT_K = 16384, AT_V = 81920, AT_TAB = 163840, AT_ONES = 230400, AT_CT = 230912;
__host__ __device__ constexpr uint32_t p3_o(int consumer, int stage) {
    return consumer == 0 ? (stage < 2 ? stage * 8192u : 147456u + (stage - 2) * 8192u) : AT_TAB + stage * 8192u;
}
constexpr uint32_t BAR = 229376;
constexpr uint32_t B_FULL = BAR, B_EMPTY = BAR + 32;
constexpr uint32_t B_KV = BAR + 96, B_Q = BAR + 160, B_CONS = BAR + 168, B_WFULL = BAR + 232;
constexpr uint32_t B_OFULL = BAR + 640;
constexpr uint32_t B_ATTDONE = BAR + 704, OFF_TICKET = BAR + 712;
constexpr uint32_t B_STFREE = BAR + 360;
constexpr uint32_t OFF_MAX = BAR + 416, OFF_NORM = BAR + 512;
constexpr int SMEM_BYTES = BAR + 1024 + 768;
constexpr uint32_t B_TAB = BAR + 64;
constexpr float QSCALE = 0.25f * 1.4426950408889634f;

struct Maps { CUtensorMap xA, xB, wA, wB, o, o16, woA, woB, out; };

__device__ __forceinline__ void phase_qkv(uint8_t* smem, const Maps& mp) {
    constexpr uint32_t sb = SM_BASE;
    const int tid = threadIdx.x, warp = tid >> 5, lane = tid & 31;
    const int nt = blockIdx.x & 7, mt = blockIdx.x >> 3;
    float* sMax = (float*)(smem + OFF_MAX);
    auto produce = [&](int kb) {
        const int s = kb & 3;
        const uint32_t full = sb + B_FULL + 8 * s, st = sb + s * P1_STAGE;
        mbar_expect_tx(full, P1_STAGE);
        tma_load_2d(st, kb < 8 ? &mp.xB : &mp.xA, (kb & 7) * 64, mt * 128, full);
#pragma unroll
        for (int j = 0; j < 3; j++) tma_load_2d(st + 16384 + j * 8192, kb < 8 ? &mp.wB : &mp.wA, j * 512 + nt * 64, (kb & 7) * 64, full);
    };
    if (tid == 0) {
        tma_prefetch_desc(&mp.xB); tma_prefetch_desc(&mp.wB);
        for (int i = 0; i < 4; i++) { mbar_init(sb + B_FULL + 8 * i, 1); mbar_init(sb + B_EMPTY + 8 * i, 2); }
        fence_mbar_init();
        DSTAMP(28);
        for (int kb = 0; kb < 4; kb++) produce(kb);
        DSTAMP(29);
        tma_prefetch_desc(&mp.xA); tma_prefetch_desc(&mp.wA);
    }
    if (tid == 32) {
                for (int i = 0; i < 4; i++) mbar_init(sb + B_STFREE + 8 * i, 2);
        mbar_init(sb + B_Q, 1); mbar_init(sb + B_TAB, 256);
        for (int i = 0; i < 8; i++) { mbar_init(sb + B_KV + 8 * i, 1); mbar_init(sb + B_CONS + 8 * i, 4); mbar_init(sb + B_WFULL + 8 * i, 1); }
        for (int i = 0; i < 8; i++) mbar_init(sb + B_OFULL + 8 * i, 1);
        mbar_init(sb + B_ATTDONE, 4);
        *(int*)(smem + OFF_TICKET) = 0;
        fence_mbar_init();
    }
    if (tid >= 64 && tid < 72) sMax[tid - 64] = 0.f;
    __syncthreads();
    STAMP(0, 1);

    const int wg = __shfl_sync(0xffffffffu, warp >> 2, 0);
    const int branchB = wg < 2;
    const int wh = wg & 1;
    const int kb0 = branchB ? 0 : 8;
    float acc[96];
#pragma unroll
    for (int i = 0; i < 96; i++) acc[i] = 0.f;
    fence_regs(acc);
    if (!branchB) {
        const int w = warp & 7, j = w * 32 + lane;
        const float f = (j + 0.5f) * (1.f / 256.f);
        const uint32_t val = (uint32_t)(__float2int_rn((exp2f(f) - 1.f) * 128.f) - (j >> 1) + (63 << 7) - 0x8000);
        uint4* tb = (uint4*)(smem + AT_TAB) + w * 32 * 8 + lane;
#pragma unroll
        for (int i = 0; i < 8; i++) {
            const uint32_t v = __shfl_sync(0xffffffffu, val, i * 4 + (lane >> 3));
            tb[i * 32] = make_uint4(v, v, v, v);
            tb[2048 + i * 32] = make_uint4(v << 16, v << 16, v << 16, v << 16);
        }
        if (w == 0) { for (int i = lane; i < 128; i += 32) ((uint32_t*)(smem + AT_ONES))[i] = 0x3F803F80u; }
        if (w == 1) {
            for (int i = lane; i < 64; i += 32) {
                const int r = i >> 3, ww = i & 7, chunk = (ww >> 2) ^ (r >> 2);
                ((uint32_t*)(smem + AT_CT))[i] = (chunk == 0 && (ww & 3) == 0) ? 0x000043A0u : 0u;
            }
        }
        fence_async_smem();
        mbar_arrive(sb + B_TAB);
        named_bar(3, 512);
    }
    const uint64_t dA0 = mk_desc(DESC_SW128, sb + wh * 8192, 16, 1024);
#pragma unroll
    for (int i = 0; i < 8; i++) {
        const int kb = kb0 + i, s = i & 3;
        mbar_wait(sb + B_FULL + 8 * s, (i >> 2) & 1);
        if (kb == 0) STAMP(0, 2);
        if ((tid & 255) == 0) DSTAMP(kb);
        const uint64_t dA = dA0 + (uint64_t)(s * (P1_STAGE >> 4)), dB = mk_desc(DESC_SW128, sb + s * P1_STAGE + 16384, 8192, 1024);
        wg_fence();
#pragma unroll
        for (int k = 0; k < 4; k++) wgmma_ss_n192_tb(acc, dA + k * 2, dB + k * 128, 1);
        wg_commit();
        if (i == 7 && branchB) asm volatile("bar.arrive 3, 512;" ::: "memory");
        if (i > 0) {
            wg_wait<1>();
            if (i >= 5 && !branchB && (tid & 127) == 0) mbar_arrive(sb + B_STFREE + 8 * (i - 5));
            if (kb + 3 < 16) {
                const uint32_t eb = sb + B_EMPTY + 8 * ((i - 1) & 3);
                if ((tid & 127) == 0) {
                    mbar_arrive(eb);
                    if (wh == 0) { mbar_wait(eb, ((i - 1) >> 2) & 1); produce(kb + 3); }
                }
                __syncwarp();
            }
        }
    }
    wg_wait<0>();
    fence_regs(acc);
    STAMP(0, 3);

    const int wq = warp & 3, g = lane >> 2, t = lane & 3;
    const int lr = (lane & 7) + ((lane >> 3) & 1) * 8;
    const int lc = lane >> 4;
    const int row0 = mt * 128;
    const int w8 = warp & 7;
    if (branchB) {
        {
            const uint32_t eb = sb + B_EMPTY + 8 * 3;
            if ((tid & 127) == 0) {
                mbar_arrive(eb);
                if (wh == 0) { mbar_wait(eb, 1); produce(11); }
            }
            __syncwarp();
        }
        const int orow = g + (t >> 1) * 8;
        const uint32_t ooff = (uint32_t)(row0 + wh * 64 + wq * 16 + orow) * 32 + (((t & 1) ^ ((orow & 7) >> 2)) << 4);
        const bool o1 = t & 1, o2 = t & 2;
        uint32_t mymax = 0;
#pragma unroll
        for (int sl = 0; sl < 12; sl++) {
            float* a = acc + sl * 8;
            if (sl < 4) {
#pragma unroll
                for (int i = 0; i < 8; i++) a[i] *= QSCALE;
            }
            if (sl < 8) {
                const float n0 = fmaf(a[0], a[0], fmaf(a[1], a[1], fmaf(a[4], a[4], a[5] * a[5])));
                const float n1 = fmaf(a[2], a[2], fmaf(a[3], a[3], fmaf(a[6], a[6], a[7] * a[7])));
                const uint32_t m = __reduce_max_sync(0xffffffffu, __float_as_uint(fmaxf(n0, n1)));
                if (lane == sl) mymax = m;
            }
            const uint32_t w0 = pack_bf16(a[0], a[1]), w2 = pack_bf16(a[2], a[3]), w1 = pack_bf16(a[4], a[5]), w3 = pack_bf16(a[6], a[7]);
            const uint32_t r0 = __shfl_xor_sync(0xffffffffu, o1 ? w0 : w1, 1), r1 = __shfl_xor_sync(0xffffffffu, o1 ? w2 : w3, 1);
            const uint32_t x0 = o1 ? r0 : w0, x1 = o1 ? w1 : r0, y0 = o1 ? r1 : w2, y1 = o1 ? w3 : r1;
            const uint32_t q0 = __shfl_xor_sync(0xffffffffu, o2 ? x0 : y0, 2), q1 = __shfl_xor_sync(0xffffffffu, o2 ? x1 : y1, 2);
            uint4 val;
            val.x = o2 ? q0 : x0; val.y = o2 ? q1 : x1; val.z = o2 ? y0 : q0; val.w = o2 ? y1 : q1;
            const int ty = sl >> 2, head = nt * 4 + (sl & 3);
            uint8_t* dst = (uint8_t*)((ty == 0 ? g_qB : (ty == 1 ? g_kB : g_vB)) + (size_t)head * S_LEN * 16);
            *(uint4*)(dst + ooff) = val;
        }
        if (lane < 8) atomicMax((unsigned int*)&sMax[lane], mymax);
        named_bar(1, 256);
        if (tid == 0) DSTAMP(16);
        if (w8 == 7 && lane >= 8 && lane < 16) { const int i = lane - 8; (i < 4 ? g_qn : g_kn)[(nt * 4 + (i & 3)) * 16 + mt] = sMax[i]; }
        named_bar(1, 256);
        const int h = blockIdx.x >> 2, qb = blockIdx.x & 3;
        if (tid == 0) signal_add(&g_cnt.qkvB[nt]);
        auto ld_k = [&](int c) {
            mbar_expect_tx(sb + B_KV + 8 * c, 16384);
            bulk_g2s(sb + AT_K + c * 8192, g_kB + ((size_t)h * S_LEN + c * 256) * 16, 8192, sb + B_KV + 8 * c);
        };
        auto ld_v = [&](int c) { bulk_g2s(sb + AT_V + c * 8192, g_vB + ((size_t)h * S_LEN + c * 256) * 16, 8192, sb + B_KV + 8 * c); };
        if (tid == 32) {
            spin_ge(&g_cnt.qkvB[h >> 2], 16);
            fence_async_all();
            mbar_wait(sb + B_STFREE, 0);
            mbar_expect_tx(sb + B_Q, 16384 + 128);
            bulk_g2s(sb + AT_Q, g_qB + ((size_t)h * S_LEN + qb * 512) * 16, 16384, sb + B_Q);
            ld_k(0);
            bulk_g2s(sb + OFF_NORM, g_qn + h * 16, 64, sb + B_Q);
            bulk_g2s(sb + OFF_NORM + 64, g_kn + h * 16, 64, sb + B_Q);
            DSTAMP(27);
            mbar_wait(sb + B_STFREE + 16, 0);
            ld_v(0); ld_k(1); ld_v(1);
        }
        __syncwarp();
        STAMP(0, 5);
    } else {
        if ((tid & 127) == 0) mbar_arrive(sb + B_STFREE + 8 * 3);
        if (tid == 256) DSTAMP(22);
        named_bar(2, 256);
        const uint32_t stg = sb + P1_STGA;
        const uint32_t stAddr = stg + (wh * 64 + wq * 16 + lr) * 32 + (((lc ^ ((lr & 7) >> 2))) << 4);
#pragma unroll
        for (int sl = 0; sl < 12; sl++) {
            float* a = acc + sl * 8;
            uint32_t p0 = pack_bf16(a[0], a[1]), p1 = pack_bf16(a[2], a[3]), p2 = pack_bf16(a[4], a[5]), p3 = pack_bf16(a[6], a[7]);
            if (sl >= 4 && sl < 8) { p0 = phi_bf16x2(p0); p1 = phi_bf16x2(p1); p2 = phi_bf16x2(p2); p3 = phi_bf16x2(p3); }
            stsm_x4(stAddr + sl * 4096, p0, p1, p2, p3);
        }
        named_bar(2, 256);
        if (tid == 256) DSTAMP(23);
#pragma unroll
        for (int sl = 0; sl < 4; sl++)
            *(uint4*)((uint8_t*)(g_qA + ((size_t)(nt * 4 + sl) * S_LEN + row0) * 16) + (tid - 256) * 16) = *(const uint4*)(smem + P1_STGA + sl * 4096 + (tid - 256) * 16);
        const int hh = w8 & 3;
        const uint32_t pkb = stg + (4 + hh) * 4096 + wh * 2048, vb = stg + (8 + hh) * 4096 + wh * 2048;
        float kv0[4] = {0.f, 0.f, 0.f, 0.f}, kv1[4] = {0.f, 0.f, 0.f, 0.f}, zz[4] = {0.f, 0.f, 0.f, 0.f};
        const int ar = (lane & 7) + (lane >> 4) * 8, ac = (lane >> 3) & 1;
        const int br = (lane & 7) + ((lane >> 3) & 1) * 8, bc = lane >> 4;
#pragma unroll
        for (int ks = 0; ks < 4; ks++) {
            uint32_t af[4], bf[4];
            ldsm_x4_t(pkb + (ks * 16 + ar) * 32 + ((ac ^ ((ar & 7) >> 2)) << 4), af);
            ldsm_x4_t(vb + (ks * 16 + br) * 32 + ((bc ^ ((br & 7) >> 2)) << 4), bf);
            mma_bf16(kv0, af, bf[0], bf[1]);
            mma_bf16(kv1, af, bf[2], bf[3]);
            mma_bf16(zz, af, 0x3F803F80u, 0x3F803F80u);
        }
        if (tid == 256) DSTAMP(24);
        float* rp = (float*)(smem + P1_RED) + hh * 272;
        if (wh == 1) {
            rp[g * 16 + 2 * t] = kv0[0]; rp[g * 16 + 2 * t + 1] = kv0[1];
            rp[(g + 8) * 16 + 2 * t] = kv0[2]; rp[(g + 8) * 16 + 2 * t + 1] = kv0[3];
            rp[g * 16 + 8 + 2 * t] = kv1[0]; rp[g * 16 + 8 + 2 * t + 1] = kv1[1];
            rp[(g + 8) * 16 + 8 + 2 * t] = kv1[2]; rp[(g + 8) * 16 + 8 + 2 * t + 1] = kv1[3];
            if (t == 0) { rp[256 + g] = zz[0]; rp[256 + g + 8] = zz[2]; }
        }
        named_bar(2, 256);
        if (wh == 0) {
            float* gp = g_kvp + (size_t)(mt * NH + nt * 4 + hh) * 272;
            *(float2*)(gp + g * 16 + 2 * t) = make_float2(kv0[0] + rp[g * 16 + 2 * t], kv0[1] + rp[g * 16 + 2 * t + 1]);
            *(float2*)(gp + (g + 8) * 16 + 2 * t) = make_float2(kv0[2] + rp[(g + 8) * 16 + 2 * t], kv0[3] + rp[(g + 8) * 16 + 2 * t + 1]);
            *(float2*)(gp + g * 16 + 8 + 2 * t) = make_float2(kv1[0] + rp[g * 16 + 8 + 2 * t], kv1[1] + rp[g * 16 + 8 + 2 * t + 1]);
            *(float2*)(gp + (g + 8) * 16 + 8 + 2 * t) = make_float2(kv1[2] + rp[(g + 8) * 16 + 8 + 2 * t], kv1[3] + rp[(g + 8) * 16 + 8 + 2 * t + 1]);
            if (t == 0) { gp[256 + g] = zz[0] + rp[256 + g]; gp[256 + g + 8] = zz[2] + rp[256 + g + 8]; }
        }
        STAMP(0, 6);
    }
}

constexpr int AT_NT = 64;
#define AT_NP_V 32
#define AT_NP2_V 40
constexpr int AT_NP = AT_NP_V, AT_NP2 = AT_NP2_V;
constexpr float AT_SAFE2 = 56.f * 56.f;

__device__ __forceinline__ uint32_t ex2_tab2(float ya, float yb, uint32_t lane4) {
    const uint32_t a = __float_as_uint(ya), b = __float_as_uint(yb);
    uint32_t aa, ab, ta, tb, L;
    asm("lop3.b32 %0, %1, 0x7F80, %2, 0xEA;" : "=r"(aa) : "r"(a), "r"(lane4));
    asm("lop3.b32 %0, %1, 0x7F80, %2, 0xEA;" : "=r"(ab) : "r"(b), "r"(lane4));
    asm volatile("ld.shared.u32 %0, [%1+%2];" : "=r"(ta) : "r"(aa), "n"(SM_BASE + AT_TAB));
    asm volatile("ld.shared.u32 %0, [%1+%2];" : "=r"(tb) : "r"(ab), "n"(SM_BASE + AT_TAB + 32768));
    asm("prmt.b32 %0, %1, %2, 0x6521;" : "=r"(L) : "r"(a), "r"(b));
    return L + ta + tb;
}
template <int NT, int NP>
__device__ __forceinline__ void att_exp(const float* s, uint32_t* p, uint32_t lane4) {
    constexpr int PP = NP / 4, TOT = NT / 4;
#pragma unroll
    for (int i = 0; i < TOT; i++) {
        const int nb = (i * PP) / TOT, na = ((i + 1) * PP) / TOT;
        if (na != nb) p[nb] = ex2_tab2(s[2 * nb], s[2 * nb + 1], lane4);
        else { const int im = PP + i - nb; p[im] = pack_bf16(ex2f(s[2 * im]), ex2f(s[2 * im + 1])); }
    }
}

__device__ __forceinline__ void mbar_arrive_elect(uint32_t bar) {
    asm volatile("{.reg .pred p;\nelect.sync _|p, 0xffffffff;\n@p mbarrier.arrive.shared::cta.b64 _, [%0];\n}" ::"r"(bar) : "memory");
}
__device__ __forceinline__ void signal_add_elect(int* ptr) {
    asm volatile("{.reg .pred p;\nelect.sync _|p, 0xffffffff;\n@p red.release.gpu.global.add.s32 [%0], 1;\n}" ::"l"(ptr) : "memory");
}
__device__ __forceinline__ void load_wo_elect(const Maps& mp, int branchB, int nt, int c) {
    constexpr uint32_t sb = SM_BASE;
    const CUtensorMap* tm = branchB ? &mp.woB : &mp.woA;
    asm volatile(
        "{.reg .pred p;\n"
        "elect.sync _|p, 0xffffffff;\n"
        "@p mbarrier.arrive.expect_tx.shared::cta.b64 _, [%0], 16384;\n"
        "@p cp.async.bulk.tensor.2d.shared::cluster.global.mbarrier::complete_tx::bytes [%1], [%3, {%4, %6}], [%0];\n"
        "@p cp.async.bulk.tensor.2d.shared::cluster.global.mbarrier::complete_tx::bytes [%2], [%3, {%5, %6}], [%0];\n"
        "}" ::"r"(sb + B_WFULL + 8 * c), "r"(sb + AT_K + c * 8192), "r"(sb + AT_V + c * 8192), "l"(tm), "r"(nt * 128), "r"(nt * 128 + 64), "r"(c * 64)
        : "memory");
}
__device__ __forceinline__ void load_kv_elect(int h, int c) {
    constexpr uint32_t sb = SM_BASE;
    asm volatile(
        "{.reg .pred p;\n"
        "elect.sync _|p, 0xffffffff;\n"
        "@p mbarrier.arrive.expect_tx.shared::cta.b64 _, [%0], 16384;\n"
        "@p cp.async.bulk.shared::cluster.global.mbarrier::complete_tx::bytes [%1], [%3], 8192, [%0];\n"
        "@p cp.async.bulk.shared::cluster.global.mbarrier::complete_tx::bytes [%2], [%4], 8192, [%0];\n"
        "}" ::"r"(sb + B_KV + 8 * c), "r"(sb + AT_K + c * 8192), "r"(sb + AT_V + c * 8192),
        "l"(g_kB + ((size_t)h * S_LEN + c * 256) * 16), "l"(g_vB + ((size_t)h * S_LEN + c * 256) * 16) : "memory");
}
__device__ __forceinline__ uint32_t wait_o_ready(const int* cnt, uint32_t need) {
    int spins = 0;
    while (true) {
        int v;
        asm volatile("ld.acquire.gpu.global.s32 %0, [%1];" : "=r"(v) : "l"(cnt) : "memory");
        const uint32_t ready = __ballot_sync(0xffffffffu, v >= 4) & 0xFFu;
        __syncwarp();
        if ((ready & need) == need) { fence_async_all(); return ready; }
        if (++spins > (1 << 22)) __trap();
        __nanosleep(SPIN_NS);
    }
}
__device__ __forceinline__ void load_o_elect(const Maps& mp, int consumer, int kb, int col, int row) {
    constexpr uint32_t sb = SM_BASE;
    const uint32_t full = sb + B_OFULL + 8 * (consumer * 4 + (kb & 3));
    const uint32_t dst = sb + (consumer == 0 ? ((kb & 2) ? 147456u + (kb & 1) * 8192u : (kb & 1) * 8192u) : AT_TAB + (kb & 3) * 8192u);
    asm volatile(
        "{.reg .pred p;\n"
        "elect.sync _|p, 0xffffffff;\n"
        "@p mbarrier.arrive.expect_tx.shared::cta.b64 _, [%0], 8192;\n"
        "@p cp.async.bulk.tensor.2d.shared::cluster.global.mbarrier::complete_tx::bytes [%1], [%2, {%3, %4}], [%0];\n"
        "}" ::"r"(full), "r"(dst), "l"(&mp.o), "r"(col), "r"(row) : "memory");
}
__device__ __forceinline__ void load_wo(const Maps& mp, int branchB, int nt, int c) {
    constexpr uint32_t sb = SM_BASE;
    const CUtensorMap* tm = branchB ? &mp.woB : &mp.woA;
    mbar_expect_tx(sb + B_WFULL + 8 * c, 16384);
    tma_load_2d(sb + AT_K + c * 8192, tm, nt * 128, c * 64, sb + B_WFULL + 8 * c);
    tma_load_2d(sb + AT_V + c * 8192, tm, nt * 128 + 64, c * 64, sb + B_WFULL + 8 * c);
}

__device__ __forceinline__ bool phase_attn(uint8_t* smem, const Maps& mp) {
    constexpr uint32_t sb = SM_BASE;
    const int tid = threadIdx.x, warp = (tid >> 5) & 3, lane = tid & 31;
    const int wg = __shfl_sync(0xffffffffu, tid >> 7, 0);
    const int wwarp = __shfl_sync(0xffffffffu, warp, 0);
    const int h = blockIdx.x >> 2, qb = blockIdx.x & 3;
    constexpr int NCH = 8;
    constexpr uint32_t sK = sb + AT_K, sV = sb + AT_V, sQ = sb + AT_Q, sBar = sb + B_KV;

    __syncwarp();
    mbar_wait(sb + B_TAB, 0);
    mbar_wait(sb + B_Q, 0);
    if (wg >= 2) {
        named_bar(2, 256);
        if (wwarp < 3) load_kv_elect(h, 2 + (wg - 2) * 3 + wwarp);
    }
    __syncwarp();
    STAMP(1, 2);
    bool safe;
    {
        const float* nrm = (const float*)(smem + OFF_NORM);
        const float qv = lane < 4 ? nrm[qb * 4 + lane] : 0.f;
        const float kv = lane < 16 ? nrm[16 + lane] : 0.f;
        const uint32_t qm = __reduce_max_sync(0xffffffffu, __float_as_uint(qv));
        const uint32_t km = __reduce_max_sync(0xffffffffu, __float_as_uint(kv));
        safe = (__uint_as_float(qm) * __uint_as_float(km) * (16.f * 1.05f) < AT_SAFE2);
    }
    const uint64_t dK0 = mk_desc(DESC_SW32, sK, 16, 256);
    const uint64_t dC = mk_desc(DESC_SW32, sb + AT_CT, 16, 0);
    const uint64_t dV0 = mk_desc(DESC_SW32, sV, AT_ONES - AT_V, 256);
    constexpr int64_t VSTEP = 32 - (32 << 16);
    const uint32_t lane4 = lane * 4;
    const uint32_t aone[4] = {(lane & 3) == 0 ? 0x00003F80u : 0u, (lane & 3) == 0 ? 0x00003F80u : 0u, 0u, 0u};
    const int g = lane >> 2, t = lane & 3;
    constexpr int NT = AT_NT, NP = AT_NP;
    const int oBranch = blockIdx.x >> 6, oNt = blockIdx.x & 3;

    STAMP(1, 3);
#pragma unroll 1
    for (int qi = 0; qi < 2; qi++) {
        const int qt = wg * 2 + qi;
        const int row0 = qb * 512 + qt * 64 + warp * 16;
        uint32_t qa[4];
        ldsm_x4(sQ + (qt * 64 + warp * 16 + (lane & 7) + ((lane >> 3) & 1) * 8) * 32 + ((((lane >> 4) ^ ((lane & 7) >> 2))) << 4), qa);
        float o[12], s[NT / 2];
#pragma unroll
        for (int i = 0; i < 12; i++) o[i] = 0.f;
#pragma unroll
        for (int i = 0; i < NT / 2; i++) s[i] = 0.f;
        fence_regs(o); fence_regs(s);
        if (safe) {
            uint32_t pa[NT / 4], pb[NT / 4];
            auto issue_qk = [&](uint64_t dK, int np) {
                wgmma_rs_n64<0>(s, qa, dK);
                if (np == 24) wgmma_rs_n24<1>(s, aone, dC); else if (np == 32) wgmma_rs_n32<1>(s, aone, dC); else wgmma_rs_n40<1>(s, aone, dC);
            };
            mbar_wait(sBar, 0);
            wg_fence();
            issue_qk(dK0, NP);
            wg_commit();
            wg_wait<0>();
            fence_regs(s);
            att_exp<NT, NP>(s, pa, lane4);
            uint64_t dK = dK0, dV = dV0;
            auto step = [&](uint32_t (&pc)[NT / 4], uint32_t (&pn)[NT / 4], bool last, int jt) {
                wg_fence();
                if (!last) { issue_qk(dK + (uint64_t)(jt * NT * 2 + NT * 2), (jt & 1) ? NP : AT_NP2); wg_commit(); }
#pragma unroll
                for (int kk = 0; kk < NT / 16; kk++) wgmma_rs_n24_tb<1>(o, pc + kk * 4, dV + (uint64_t)((int64_t)(jt * (NT / 16) + kk) * VSTEP));
                wg_commit();
                if (!last) {
                    wg_wait<1>();
                    fence_regs(s);
                    if (jt & 1) att_exp<NT, NP>(s, pn, lane4); else att_exp<NT, AT_NP2>(s, pn, lane4);
                }
                wg_wait<0>();
                fence_regs(pc); fence_regs(o);
            };
            constexpr int TPC = 256 / NT;
#pragma unroll 1
            for (int cch = 0; cch < NCH; cch++) {
                const int cu = __shfl_sync(0xffffffffu, cch, 0);
                dK = dK0 + (uint64_t)(cu * 512); dV = dV0 + (uint64_t)((int64_t)(cu * 16) * VSTEP);
                asm volatile("" : "+l"(dK), "+l"(dV));
#pragma unroll
                for (int jj = 0; jj < TPC; jj += 2) {
                    step(pa, pb, false, jj);
                    if (jj + 2 == TPC) {
                        if (cch == NCH - 1) break;
                        mbar_wait(sBar + 8 * (cch + 1), 0);
                    }
                    step(pb, pa, false, jj + 1);
                    if (jj == 0 && qi == 0 && cch == 0 && wg == 2 && wwarp == 0) {
                        signal_add_elect(&g_cnt.qkvA[blockIdx.x & 7]);
                    }
                }
                if (qi == 1 && cch == 0) {
                    named_bar(4 + wg, 128);
                    if (wwarp == 0) signal_add_elect(&g_cnt.oB[((qb * 4 + wg) * 2) * 8 + (h >> 2)]);
                }
                if (qi == 1 && cch == 5 && oBranch && wg == 3 && wwarp == 1) {
                    const int omt = (blockIdx.x & 63) >> 2;
                    wait_o_ready(&g_cnt.oB[(omt * 2) * 8 + (lane & 7)], 0xFFu);
                    mbar_wait(sb + B_CONS, 0);
                    for (int kb = 0; kb < 4; kb++) load_o_elect(mp, 0, kb, 512 + kb * 64, omt * 128);
                }
                if (qi == 1 && wwarp == 0 && cch < NCH - 1) {
                    mbar_arrive_elect(sb + B_CONS + 8 * cch);
                    if (cch >= 1 && wg == ((cch - 1) & 3)) { mbar_wait(sb + B_CONS + 8 * (cch - 1), 0); load_wo_elect(mp, oBranch, oNt, cch - 1); }
                }
            }
            dV = dV0 + (uint64_t)((int64_t)(7 * 16) * VSTEP);
            step(pb, pa, true, TPC - 1);
            if (qi == 1 && wwarp == 0) {
                mbar_arrive_elect(sb + B_CONS + 8 * 7);
                if (wg == 2) { mbar_wait(sb + B_CONS + 8 * 6, 0); load_wo_elect(mp, oBranch, oNt, 6); }
                if (wg == 3) { mbar_wait(sb + B_CONS + 8 * 7, 0); load_wo_elect(mp, oBranch, oNt, 7); }
            }
        } else {
            if (qi == 0 && tid == 256) signal_add(&g_cnt.qkvA[blockIdx.x & 7]);
            float m0 = -INFINITY, m1 = -INFINITY;
            uint32_t p[NT / 4];
#pragma unroll 1
            for (int j = 0; j < S_LEN / NT; j++) {
                if ((j * NT) % 256 == 0) mbar_wait(sBar + 8 * ((j * NT) / 256), 0);
                wg_fence();
                wgmma_rs_n64<0>(s, qa, dK0 + (uint64_t)(j * NT * 2));
                wg_commit();
                wg_wait<0>();
                fence_regs(s); fence_regs(o);
                float t0 = m0, t1 = m1;
#pragma unroll
                for (int i = 0; i < NT / 2; i += 4) { t0 = fmaxf(t0, fmaxf(s[i], s[i + 1])); t1 = fmaxf(t1, fmaxf(s[i + 2], s[i + 3])); }
                t0 = fmaxf(t0, __shfl_xor_sync(0xffffffffu, t0, 1)); t0 = fmaxf(t0, __shfl_xor_sync(0xffffffffu, t0, 2));
                t1 = fmaxf(t1, __shfl_xor_sync(0xffffffffu, t1, 1)); t1 = fmaxf(t1, __shfl_xor_sync(0xffffffffu, t1, 2));
                const float r0 = ex2f(m0 - t0), r1 = ex2f(m1 - t1);
                m0 = t0; m1 = t1;
#pragma unroll
                for (int i = 0; i < 12; i += 4) { o[i] *= r0; o[i + 1] *= r0; o[i + 2] *= r1; o[i + 3] *= r1; }
#pragma unroll
                for (int i = 0; i < NT / 4; i += 2) {
                    p[i] = pack_bf16(ex2f(s[2 * i] - m0), ex2f(s[2 * i + 1] - m0));
                    p[i + 1] = pack_bf16(ex2f(s[2 * i + 2] - m1), ex2f(s[2 * i + 3] - m1));
                }
                fence_regs(o);
                wg_fence();
#pragma unroll
                for (int kk = 0; kk < NT / 16; kk++) wgmma_rs_n24_tb<1>(o, p + kk * 4, dV0 + (uint64_t)((int64_t)(j * (NT / 16) + kk) * VSTEP));
                wg_commit();
                wg_wait<0>();
                fence_regs(p);
            }
            fence_regs(o);
        }
        const float l0 = 1.f / o[8], l1 = 1.f / o[10];
        uint32_t* op0 = (uint32_t*)(g_o + (size_t)(row0 + g) * 1024 + 512 + h * 16);
        uint32_t* op1 = (uint32_t*)(g_o + (size_t)(row0 + g + 8) * 1024 + 512 + h * 16);
        op0[t] = pack_bf16(o[0] * l0, o[1] * l0);
        op0[4 + t] = pack_bf16(o[4] * l0, o[5] * l0);
        op1[t] = pack_bf16(o[2] * l1, o[3] * l1);
        op1[4 + t] = pack_bf16(o[6] * l1, o[7] * l1);
        if (!safe && qi == 0) {
            named_bar(4 + wg, 128);
            if ((tid & 127) == 0) signal_add(&g_cnt.oB[((qb * 4 + wg) * 2) * 8 + (h >> 2)]);
        }
    }
    named_bar(4 + wg, 128);
    if ((tid & 127) == 0) signal_add(&g_cnt.oB[((qb * 4 + wg) * 2 + 1) * 8 + (h >> 2)]);
    STAMP(1, 4);
    if (wwarp == 0) mbar_arrive_elect(sb + B_ATTDONE);
    if (!safe && tid == 0) {
        mbar_wait(sb + B_ATTDONE, 0);
        for (int c = 0; c < 8; c++) load_wo(mp, oBranch, oNt, c);
    }
    __syncwarp();
    return safe;
}

__device__ __forceinline__ void phase_out(uint8_t* smem, const Maps& mp, bool safe) {
    constexpr uint32_t sb = SM_BASE;
    const int tid = threadIdx.x, warp = tid >> 5, lane = tid & 31;
    const int branchB = blockIdx.x >> 6;
    const int mt = (blockIdx.x & 63) >> 2, nt = blockIdx.x & 3;
    const int wg = __shfl_sync(0xffffffffu, warp >> 2, 0);
    if (wg >= 2) return;
    const int wwarp = __shfl_sync(0xffffffffu, warp & 3, 0);
    const int col0 = branchB * 512, row0 = mt * 128 + wg * 64;
    const int* cnt = branchB ? &g_cnt.oB[(mt * 2 + wg) * 8 + (lane & 7)] : &g_cnt.oA;
    const bool prefetched = wg == 0 && branchB && safe;
    uint32_t ready = prefetched ? 0xFFu : 0u;
    if (wwarp == 0 && !prefetched) {
        if (wg == 0) { if (lane == 0) { tma_prefetch_desc(&mp.o); tma_prefetch_desc(&mp.out); } }
        mbar_wait(sb + B_ATTDONE, 0);
#pragma unroll 1
        for (int kb = 0; kb < 4; kb++) {
            if (!((ready >> kb) & 1)) ready = wait_o_ready(cnt, 1u << kb);
            load_o_elect(mp, wg, kb, col0 + kb * 64, row0);
        }
    }
    float acc[64];
#pragma unroll
    for (int i = 0; i < 64; i++) acc[i] = 0.f;
    fence_regs(acc);
    const uint64_t dA0 = mk_desc(DESC_SW128, sb, 16, 1024);
#pragma unroll
    for (int kb = 0; kb < 8; kb++) {
        const int s = kb & 3;
        mbar_wait(sb + B_WFULL + 8 * kb, 0);
        mbar_wait(sb + B_OFULL + 8 * (wg * 4 + s), kb >> 2);
        if (kb == 0) STAMP(2, 2);
        const uint64_t dA = dA0 + (uint64_t)((wg == 0 ? p3_o(0, s) : p3_o(1, s)) >> 4);
        const uint64_t dB = mk_desc(DESC_SW128, sb + AT_K + kb * 8192, AT_V - AT_K, 1024);
        wg_fence();
#pragma unroll
        for (int k = 0; k < 4; k++) wgmma_ss_n128_tb(acc, dA + k * 2, dB + k * 128, 1);
        wg_commit();
        if (kb >= 1 && kb <= 4) {
            wg_wait<1>();
            if (wwarp == 0) {
                if (!((ready >> (kb + 3)) & 1)) ready = wait_o_ready(cnt, 1u << (kb + 3));
                load_o_elect(mp, wg, kb + 3, col0 + (kb + 3) * 64, row0);
                if (kb == 4 && lane == 0) {
                    if (atomicAdd((int*)(smem + OFF_TICKET), 1) == 1) finish_ticket();
                }
                __syncwarp();
            }
        }
    }
    wg_wait<0>();
    fence_regs(acc);
    STAMP(2, 3);
    const int wq = warp & 3;
    const uint32_t stg = sb + (wg == 0 ? p3_o(0, 0) : p3_o(1, 0));
    const int lr = wq * 16 + (lane & 7) + ((lane >> 3) & 1) * 8, lc = lane >> 4;
#pragma unroll
    for (int j = 0; j < 8; j++) {
        const float* a = acc + j * 8;
        const int chunk = (j & 3) * 2 + lc;
        stsm_x4(stg + (j >> 2) * 8192 + lr * 128 + ((chunk ^ (lr & 7)) << 4),
                pack_bf16(a[0], a[1]), pack_bf16(a[2], a[3]), pack_bf16(a[4], a[5]), pack_bf16(a[6], a[7]));
    }
    fence_async_smem();
    named_bar(4 + wg, 128);
    if ((tid & 127) < 2) {
        const int j = tid & 1;
        tma_store_2d(&mp.out, stg + j * 8192, branchB * 512 + nt * 128 + j * 64, mt * 128 + wg * 64);
        bulk_commit();
        asm volatile("cp.async.bulk.wait_group.read 0;" ::: "memory");
    }
    STAMP(2, 4);
}

__device__ __noinline__ void linattn_mid(uint8_t* smem, int cta, const CUtensorMap* tmO16) {
    constexpr uint32_t sb = SM_BASE;
    const int tid = threadIdx.x, warp = tid >> 5, lane = tid & 31;
    constexpr int NBUF = 4;
    const uint32_t sBar = sb;
    const uint32_t sQ0 = sb + 1024;
    const uint32_t sSt = sQ0 + NBUF * 32768;
    float* skv = (float*)(smem + 1024 + NBUF * 32768 + 65536);
    if (tid == 0) { for (int i = 0; i < NBUF; i++) { mbar_init(sBar + 8 * i, 1); mbar_init(sBar + 64 + 8 * i, 16); } fence_mbar_init(); }
    __syncthreads();
    if (warp == 0 && lane == 0) { spin_ge(&g_cnt.qkvA[2 * cta], 16); spin_ge(&g_cnt.qkvA[2 * cta + 1], 16); finish_ticket(); }
    __syncthreads();
    if (lane == 0) fence_async_all();
    __syncwarp();
    STAMP(1, 2);
    auto load_chunk = [&](int c, int j) {
        bulk_g2s(sQ0 + (c % NBUF) * 32768 + j * 8192, g_qA + ((size_t)(cta * 8 + (c >> 3) * 4 + j) * S_LEN + (c & 7) * 256) * 16, 8192, sBar + 8 * (c % NBUF));
    };
    if (lane == 0 && warp < NBUF) {
        mbar_expect_tx(sBar + 8 * warp, 32768);
        for (int j = 0; j < 4; j++) load_chunk(warp, j);
    }
    for (int i = tid; i < 8 * 68; i += 512) {
        const int hh = i / 68, e = i - hh * 68;
        const float* gp = g_kvp + (size_t)(cta * 8 + hh) * 272 + e * 4;
        float4 v0, v1, v2, v3, v4, v5, v6, v7;
#define LD4(m) (*(const float4*)(gp + (size_t)(m) * NH * 272))
#define ADD4(a, b) (a).x += (b).x, (a).y += (b).y, (a).z += (b).z, (a).w += (b).w
        v0 = LD4(0); v1 = LD4(1); v2 = LD4(2); v3 = LD4(3); v4 = LD4(4); v5 = LD4(5); v6 = LD4(6); v7 = LD4(7);
        {
            const float4 w0 = LD4(8), w1 = LD4(9), w2 = LD4(10), w3 = LD4(11), w4 = LD4(12), w5 = LD4(13), w6 = LD4(14), w7 = LD4(15);
            ADD4(v0, w0); ADD4(v1, w1); ADD4(v2, w2); ADD4(v3, w3); ADD4(v4, w4); ADD4(v5, w5); ADD4(v6, w6); ADD4(v7, w7);
        }
        ADD4(v0, v4); ADD4(v1, v5); ADD4(v2, v6); ADD4(v3, v7); ADD4(v0, v2); ADD4(v1, v3); ADD4(v0, v1);
#undef LD4
#undef ADD4
        *(float4*)(skv + i * 4) = v0;
    }
    __syncthreads();
    STAMP(1, 3);
    const int g = lane >> 2, t = lane & 3;
    const int lr = (lane & 7) + ((lane >> 3) & 1) * 8, lc = lane >> 4;
    const uint32_t loff = (warp * 16 + lr) * 32 + ((lc ^ ((lr & 7) >> 2)) << 4);
#pragma unroll 1
    for (int quad = 0; quad < 2; quad++) {
        uint32_t bf[4][6];
#pragma unroll
        for (int j = 0; j < 4; j++) {
            const float* kv = skv + (quad * 4 + j) * 272;
            bf[j][0] = pack_bf16(kv[(2 * t) * 16 + g], kv[(2 * t + 1) * 16 + g]);
            bf[j][1] = pack_bf16(kv[(2 * t + 8) * 16 + g], kv[(2 * t + 9) * 16 + g]);
            bf[j][2] = pack_bf16(kv[(2 * t) * 16 + 8 + g], kv[(2 * t + 1) * 16 + 8 + g]);
            bf[j][3] = pack_bf16(kv[(2 * t + 8) * 16 + 8 + g], kv[(2 * t + 9) * 16 + 8 + g]);
            bf[j][4] = pack_bf16(kv[256 + 2 * t], kv[256 + 2 * t + 1]);
            bf[j][5] = pack_bf16(kv[256 + 2 * t + 8], kv[256 + 2 * t + 9]);
        }
#pragma unroll 1
        for (int rc = 0; rc < 8; rc++) {
            const int c = quad * 8 + rc;
            mbar_wait(sBar + 8 * (c % NBUF), (c / NBUF) & 1);
            const uint32_t qb = sQ0 + (c % NBUF) * 32768 + loff;
            const uint32_t stg = sSt + (c & 1) * 32768 + warp * 2048;
            uint32_t a[4][4];
#pragma unroll
            for (int j = 0; j < 4; j++) ldsm_x4(qb + j * 8192, a[j]);
            __syncwarp();
            if (lane == 0) {
                mbar_arrive(sBar + 64 + 8 * (c % NBUF));
                if (c >= 1 && warp == (c & 15) && c - 1 + NBUF < 16) {
                    const int cp = c - 1;
                    mbar_wait(sBar + 64 + 8 * (cp % NBUF), (cp / NBUF) & 1);
                    mbar_expect_tx(sBar + 8 * (cp % NBUF), 32768);
                    for (int j = 0; j < 4; j++) load_chunk(cp + NBUF, j);
                }
                if (c >= 2) asm volatile("cp.async.bulk.wait_group.read 1;" ::: "memory");
            }
            __syncwarp();
#pragma unroll
            for (int j = 0; j < 4; j++) {
#pragma unroll
                for (int i = 0; i < 4; i++) a[j][i] = phi_bf16x2(a[j][i]);
                float n0[4] = {0.f, 0.f, 0.f, 0.f}, n1[4] = {0.f, 0.f, 0.f, 0.f}, dn[4] = {0.f, 0.f, 0.f, 0.f};
                mma_bf16(n0, a[j], bf[j][0], bf[j][1]);
                mma_bf16(n1, a[j], bf[j][2], bf[j][3]);
                mma_bf16(dn, a[j], bf[j][4], bf[j][5]);
                const float i0 = rcp_fast(dn[0] + 1e-6f), i1 = rcp_fast(dn[2] + 1e-6f);
                stsm_x4(stg + lr * 128 + (((j * 2 + lc) ^ (lr & 7)) << 4),
                        pack_bf16(n0[0] * i0, n0[1] * i0), pack_bf16(n0[2] * i1, n0[3] * i1),
                        pack_bf16(n1[0] * i0, n1[1] * i0), pack_bf16(n1[2] * i1, n1[3] * i1));
            }
            fence_async_smem();
            __syncwarp();
            if (lane == 0) {
                tma_store_2d(tmO16, stg, cta * 128 + quad * 64, rc * 256 + warp * 16);
                bulk_commit();
            }
        }
    }
    if (lane == 0) { bulk_wait0(); fence_async_all(); }
    __syncthreads();
    if (tid == 0) signal_add(&g_cnt.oA);
    STAMP(1, 5);
}

__global__ void __launch_bounds__(512, 1) fused_kernel(const __grid_constant__ Maps mp) {
    extern __shared__ __align__(1024) uint8_t smem[];
    if (smem_u32(smem) != SM_BASE) __trap();
    STAMP(0, 0);
    if (blockIdx.x >= 128) {
        linattn_mid(smem, blockIdx.x - 128, &mp.o16);
    } else {
        phase_qkv(smem, mp);
        STAMP(1, 1);
        const bool safe = phase_attn(smem, mp);
        phase_out(smem, mp, safe);
    }
}

typedef CUresult (*EncodeFn)(CUtensorMap*, CUtensorMapDataType, cuuint32_t, void*, const cuuint64_t*, const cuuint64_t*,
                             const cuuint32_t*, const cuuint32_t*, CUtensorMapInterleave, CUtensorMapSwizzle,
                             CUtensorMapL2promotion, CUtensorMapFloatOOBfill);

void make_map(EncodeFn enc, CUtensorMap* tm, const void* ptr, uint64_t cols, uint64_t rows, uint32_t boxc, uint32_t boxr) {
    cuuint64_t dims[2] = {cols, rows};
    cuuint64_t strides[1] = {cols * 2};
    cuuint32_t box[2] = {boxc, boxr};
    cuuint32_t es[2] = {1, 1};
    enc(tm, CU_TENSOR_MAP_DATA_TYPE_BFLOAT16, 2, const_cast<void*>(ptr), dims, strides, box, es, CU_TENSOR_MAP_INTERLEAVE_NONE,
        CU_TENSOR_MAP_SWIZZLE_128B, CU_TENSOR_MAP_L2_PROMOTION_L2_256B, CU_TENSOR_MAP_FLOAT_OOB_FILL_NONE);
}

struct HostState {
    bool init;
    const void* key[7];
    Maps mp;
};
HostState g_hs;

}

extern "C" void kernel_launch(void* const* d_in, const int* in_sizes, int n_in, void* d_out, int out_size) {
    (void)in_sizes; (void)n_in; (void)out_size;
    HostState& hs = g_hs;
    bool same = hs.init && hs.key[6] == d_out;
    for (int i = 0; i < 6 && same; i++) same = hs.key[i] == d_in[i];
    if (!same) {
        void* fn = nullptr;
        cudaDriverEntryPointQueryResult qr;
        cudaGetDriverEntryPoint("cuTensorMapEncodeTiled", &fn, cudaEnableDefault, &qr);
        EncodeFn enc = (EncodeFn)fn;
        void* po = nullptr;
        cudaGetSymbolAddress(&po, g_o);
        make_map(enc, &hs.mp.xA, d_in[0], 512, 2048, 64, 128);
        make_map(enc, &hs.mp.wA, d_in[1], 1536, 512, 64, 64);
        make_map(enc, &hs.mp.woA, d_in[2], 512, 512, 64, 64);
        make_map(enc, &hs.mp.xB, d_in[3], 512, 2048, 64, 128);
        make_map(enc, &hs.mp.wB, d_in[4], 1536, 512, 64, 64);
        make_map(enc, &hs.mp.woB, d_in[5], 512, 512, 64, 64);
        make_map(enc, &hs.mp.o, po, 1024, 2048, 64, 64);
        make_map(enc, &hs.mp.o16, po, 1024, 2048, 64, 16);
        make_map(enc, &hs.mp.out, d_out, 1024, 2048, 64, 64);
        cudaFuncSetAttribute(fused_kernel, cudaFuncAttributeMaxDynamicSharedMemorySize, SMEM_BYTES);
        for (int i = 0; i < 6; i++) hs.key[i] = d_in[i];
        hs.key[6] = d_out;
        hs.init = true;
    }
    fused_kernel<<<132, 512, SMEM_BYTES, cudaStreamPerThread>>>(hs.mp);
}
```

```cpp
#include <cuda_runtime.h>
#include <cuda_bf16.h>
#include <cuda.h>
#include <stdint.h>

namespace {

constexpr int S_LEN = 2048;
constexpr int NH = 32;

__device__ __align__(1024) uint16_t g_qB[NH * S_LEN * 16];
__device__ __align__(1024) uint16_t g_kB[NH * S_LEN * 16];
__device__ __align__(1024) uint16_t g_vB[NH * S_LEN * 16];
__device__ __align__(1024) uint16_t g_qA[NH * S_LEN * 16];
__device__ __align__(1024) uint16_t g_o[S_LEN * 1024];
__device__ __align__(16) float g_kvp[16 * NH * 272];
__device__ __align__(64) float g_qn[NH * 16];
__device__ __align__(64) float g_kn[NH * 16];

struct Counters {
    int qkvB[8];
    int qkvA[8];
    int oB[16 * 8];
    int oA;
    int done;
};
__device__ Counters g_cnt;

#define STAMP(k, s) do {} while (0)
#define DSTAMP(i) do {} while (0)

__device__ __forceinline__ uint32_t smem_u32(const void* p) { return (uint32_t)__cvta_generic_to_shared(p); }
__device__ __forceinline__ void wg_fence() { asm volatile("wgmma.fence.sync.aligned;" ::: "memory"); }
__device__ __forceinline__ void wg_commit() { asm volatile("wgmma.commit_group.sync.aligned;" ::: "memory"); }
template <int N> __device__ __forceinline__ void wg_wait() { asm volatile("wgmma.wait_group.sync.aligned %0;" ::"n"(N) : "memory"); }
__device__ __forceinline__ void mbar_init(uint32_t bar, uint32_t cnt) { asm volatile("mbarrier.init.shared::cta.b64 [%0], %1;" ::"r"(bar), "r"(cnt)); }
__device__ __forceinline__ void mbar_expect_tx(uint32_t bar, uint32_t bytes) {
    asm volatile("mbarrier.arrive.expect_tx.shared::cta.b64 _, [%0], %1;" ::"r"(bar), "r"(bytes) : "memory");
}
__device__ __forceinline__ void mbar_wait(uint32_t bar, uint32_t parity) {
    asm volatile(
        "{.reg .pred p;\n"
        "WAIT_LOOP:\n"
        "mbarrier.try_wait.parity.shared::cta.b64 p, [%0], %1;\n"
        "@p bra WAIT_DONE;\n"
        "bra WAIT_LOOP;\n"
        "WAIT_DONE:\n}" ::"r"(bar), "r"(parity) : "memory");
}
__device__ __forceinline__ void mbar_arrive(uint32_t bar) { asm volatile("mbarrier.arrive.shared::cta.b64 _, [%0];" ::"r"(bar) : "memory"); }
__device__ __forceinline__ void fence_mbar_init() { asm volatile("fence.mbarrier_init.release.cluster;" ::: "memory"); }
__device__ __forceinline__ void fence_async_smem() { asm volatile("fence.proxy.async.shared::cta;" ::: "memory"); }
#define SPIN_NS 100
__device__ __forceinline__ void spin_ge(const int* p, int target) {
    int it = 0;
    while (true) {
        int v;
        asm volatile("ld.acquire.gpu.global.s32 %0, [%1];" : "=r"(v) : "l"(p) : "memory");
        if (v >= target) break;
        if (++it > (1 << 22)) __trap();
        __nanosleep(SPIN_NS);
    }
}
__device__ __forceinline__ void finish_ticket() {
    if (atomicAdd(&g_cnt.done, 1) == (int)gridDim.x - 1) {
        int* c = (int*)&g_cnt;
        for (int i = 0; i < (int)(sizeof(Counters) / sizeof(int)); i++) c[i] = 0;
    }
}
__device__ __forceinline__ void signal_add(int* p) { asm volatile("red.release.gpu.global.add.s32 [%0], 1;" ::"l"(p) : "memory"); }
__device__ __forceinline__ void fence_async_all() { asm volatile("fence.proxy.async.global;" ::: "memory"); }
__device__ __forceinline__ void named_bar(int id, int n) { asm volatile("bar.sync %0, %1;" ::"r"(id), "r"(n) : "memory"); }

__device__ __forceinline__ void bulk_g2s(uint32_t dst, const void* src, uint32_t bytes, uint32_t bar) {
    asm volatile("cp.async.bulk.shared::cluster.global.mbarrier::complete_tx::bytes [%0], [%1], %2, [%3];" ::"r"(dst), "l"(src), "r"(bytes), "r"(bar) : "memory");
}
__device__ __forceinline__ void bulk_commit() { asm volatile("cp.async.bulk.commit_group;" ::: "memory"); }
__device__ __forceinline__ void bulk_wait0() { asm volatile("cp.async.bulk.wait_group 0;" ::: "memory"); }
__device__ __forceinline__ void tma_load_2d(uint32_t dst, const CUtensorMap* tm, int c0, int c1, uint32_t bar) {
    asm volatile("cp.async.bulk.tensor.2d.shared::cluster.global.mbarrier::complete_tx::bytes [%0], [%1, {%3, %4}], [%2];" ::"r"(dst), "l"(tm), "r"(bar), "r"(c0), "r"(c1) : "memory");
}
__device__ __forceinline__ void tma_store_2d(const CUtensorMap* tm, uint32_t src, int c0, int c1) {
    asm volatile("cp.async.bulk.tensor.2d.global.shared::cta.bulk_group [%0, {%2, %3}], [%1];" ::"l"(tm), "r"(src), "r"(c0), "r"(c1) : "memory");
}
__device__ __forceinline__ void tma_prefetch_desc(const CUtensorMap* tm) { asm volatile("prefetch.tensormap [%0];" ::"l"(tm) : "memory"); }

__device__ __forceinline__ uint32_t pack_bf16(float lo, float hi) {
    uint32_t r; asm("cvt.rn.bf16x2.f32 %0, %1, %2;" : "=r"(r) : "f"(hi), "f"(lo)); return r;
}
__device__ __forceinline__ float ex2f(float x) { float r; asm("ex2.approx.ftz.f32 %0, %1;" : "=f"(r) : "f"(x)); return r; }
__device__ __forceinline__ float bf_lo(uint32_t p) { return __uint_as_float(p << 16); }
__device__ __forceinline__ float bf_hi(uint32_t p) { return __uint_as_float(p & 0xFFFF0000u); }
__device__ __forceinline__ void stsm_x4(uint32_t addr, uint32_t r0, uint32_t r1, uint32_t r2, uint32_t r3) {
    asm volatile("stmatrix.sync.aligned.m8n8.x4.shared.b16 [%0], {%1,%2,%3,%4};" ::"r"(addr), "r"(r0), "r"(r1), "r"(r2), "r"(r3) : "memory");
}
__device__ __forceinline__ void ldsm_x4(uint32_t addr, uint32_t* r) {
    asm volatile("ldmatrix.sync.aligned.m8n8.x4.shared.b16 {%0,%1,%2,%3}, [%4];" : "=r"(r[0]), "=r"(r[1]), "=r"(r[2]), "=r"(r[3]) : "r"(addr) : "memory");
}
__device__ __forceinline__ void ldsm_x4_t(uint32_t addr, uint32_t* r) {
    asm volatile("ldmatrix.sync.aligned.m8n8.x4.trans.shared.b16 {%0,%1,%2,%3}, [%4];" : "=r"(r[0]), "=r"(r[1]), "=r"(r[2]), "=r"(r[3]) : "r"(addr) : "memory");
}
__device__ __forceinline__ void mma_bf16(float* d, const uint32_t* a, uint32_t b0, uint32_t b1) {
    asm volatile("mma.sync.aligned.m16n8k16.row.col.f32.bf16.bf16.f32 {%0,%1,%2,%3}, {%4,%5,%6,%7}, {%8,%9}, {%0,%1,%2,%3};"
                 : "+f"(d[0]), "+f"(d[1]), "+f"(d[2]), "+f"(d[3]) : "r"(a[0]), "r"(a[1]), "r"(a[2]), "r"(a[3]), "r"(b0), "r"(b1));
}
__device__ __forceinline__ uint32_t phi_bf16x2(uint32_t p) {
    const float t0 = bf_lo(p), t1 = bf_hi(p);
    const float a0 = fmaf(t0 + fabsf(t0), 0.5f, ex2f((t0 - fabsf(t0)) * 0.7213475204444817f));
    const float a1 = fmaf(t1 + fabsf(t1), 0.5f, ex2f((t1 - fabsf(t1)) * 0.7213475204444817f));
    const uint32_t a = pack_bf16(a0, a1);
    uint32_t r;
    asm("add.rn.bf16x2 %0, %1, %2;" : "=r"(r) : "r"(a), "r"(0x35863586u));
    return r;
}
__device__ __forceinline__ float rcp_fast(float x) { float r; asm("rcp.approx.ftz.f32 %0, %1;" : "=f"(r) : "f"(x)); return r; }
template <typename T, int N> __device__ __forceinline__ void fence_regs(T (&r)[N]) {
#pragma unroll
    for (int i = 0; i < N; i++) {
        if constexpr (sizeof(T) == 4 && T(0.5) != T(0)) asm volatile("" : "+f"(r[i])::"memory");
        else asm volatile("" : "+r"(r[i])::"memory");
    }
}

__device__ __forceinline__ void wgmma_ss_n192_tb(float* d, uint64_t da, uint64_t db, int sd) {
  asm volatile("{.reg .pred p; setp.ne.b32 p, %98, 0; wgmma.mma_async.sync.aligned.m64n192k16.f32.bf16.bf16 {%0,%1,%2,%3,%4,%5,%6,%7,%8,%9,%10,%11,%12,%13,%14,%15,%16,%17,%18,%19,%20,%21,%22,%23,%24,%25,%26,%27,%28,%29,%30,%31,%32,%33,%34,%35,%36,%37,%38,%39,%40,%41,%42,%43,%44,%45,%46,%47,%48,%49,%50,%51,%52,%53,%54,%55,%56,%57,%58,%59,%60,%61,%62,%63,%64,%65,%66,%67,%68,%69,%70,%71,%72,%73,%74,%75,%76,%77,%78,%79,%80,%81,%82,%83,%84,%85,%86,%87,%88,%89,%90,%91,%92,%93,%94,%95}, %96, %97, p, 1, 1, 0, 1;}"
    : "+f"(d[0]), "+f"(d[1]), "+f"(d[2]), "+f"(d[3]), "+f"(d[4]), "+f"(d[5]), "+f"(d[6]), "+f"(d[7]), "+f"(d[8]), "+f"(d[9]), "+f"(d[10]), "+f"(d[11]), "+f"(d[12]), "+f"(d[13]), "+f"(d[14]), "+f"(d[15]), "+f"(d[16]), "+f"(d[17]), "+f"(d[18]), "+f"(d[19]), "+f"(d[20]), "+f"(d[21]), "+f"(d[22]), "+f"(d[23]), "+f"(d[24]), "+f"(d[25]), "+f"(d[26]), "+f"(d[27]), "+f"(d[28]), "+f"(d[29]), "+f"(d[30]), "+f"(d[31]), "+f"(d[32]), "+f"(d[33]), "+f"(d[34]), "+f"(d[35]), "+f"(d[36]), "+f"(d[37]), "+f"(d[38]), "+f"(d[39]), "+f"(d[40]), "+f"(d[41]), "+f"(d[42]), "+f"(d[43]), "+f"(d[44]), "+f"(d[45]), "+f"(d[46]), "+f"(d[47]), "+f"(d[48]), "+f"(d[49]), "+f"(d[50]), "+f"(d[51]), "+f"(d[52]), "+f"(d[53]), "+f"(d[54]), "+f"(d[55]), "+f"(d[56]), "+f"(d[57]), "+f"(d[58]), "+f"(d[59]), "+f"(d[60]), "+f"(d[61]), "+f"(d[62]), "+f"(d[63]), "+f"(d[64]), "+f"(d[65]), "+f"(d[66]), "+f"(d[67]), "+f"(d[68]), "+f"(d[69]), "+f"(d[70]), "+f"(d[71]), "+f"(d[72]), "+f"(d[73]), "+f"(d[74]), "+f"(d[75]), "+f"(d[76]), "+f"(d[77]), "+f"(d[78]), "+f"(d[79]), "+f"(d[80]), "+f"(d[81]), "+f"(d[82]), "+f"(d[83]), "+f"(d[84]), "+f"(d[85]), "+f"(d[86]), "+f"(d[87]), "+f"(d[88]), "+f"(d[89]), "+f"(d[90]), "+f"(d[91]), "+f"(d[92]), "+f"(d[93]), "+f"(d[94]), "+f"(d[95]) : "l"(da), "l"(db), "r"(sd));
}
__device__ __forceinline__ void wgmma_ss_n128_tb(float* d, uint64_t da, uint64_t db, int sd) {
  asm volatile("{.reg .pred p; setp.ne.b32 p, %66, 0; wgmma.mma_async.sync.aligned.m64n128k16.f32.bf16.bf16 {%0,%1,%2,%3,%4,%5,%6,%7,%8,%9,%10,%11,%12,%13,%14,%15,%16,%17,%18,%19,%20,%21,%22,%23,%24,%25,%26,%27,%28,%29,%30,%31,%32,%33,%34,%35,%36,%37,%38,%39,%40,%41,%42,%43,%44,%45,%46,%47,%48,%49,%50,%51,%52,%53,%54,%55,%56,%57,%58,%59,%60,%61,%62,%63}, %64, %65, p, 1, 1, 0, 1;}"
    : "+f"(d[0]), "+f"(d[1]), "+f"(d[2]), "+f"(d[3]), "+f"(d[4]), "+f"(d[5]), "+f"(d[6]), "+f"(d[7]), "+f"(d[8]), "+f"(d[9]), "+f"(d[10]), "+f"(d[11]), "+f"(d[12]), "+f"(d[13]), "+f"(d[14]), "+f"(d[15]), "+f"(d[16]), "+f"(d[17]), "+f"(d[18]), "+f"(d[19]), "+f"(d[20]), "+f"(d[21]), "+f"(d[22]), "+f"(d[23]), "+f"(d[24]), "+f"(d[25]), "+f"(d[26]), "+f"(d[27]), "+f"(d[28]), "+f"(d[29]), "+f"(d[30]), "+f"(d[31]), "+f"(d[32]), "+f"(d[33]), "+f"(d[34]), "+f"(d[35]), "+f"(d[36]), "+f"(d[37]), "+f"(d[38]), "+f"(d[39]), "+f"(d[40]), "+f"(d[41]), "+f"(d[42]), "+f"(d[43]), "+f"(d[44]), "+f"(d[45]), "+f"(d[46]), "+f"(d[47]), "+f"(d[48]), "+f"(d[49]), "+f"(d[50]), "+f"(d[51]), "+f"(d[52]), "+f"(d[53]), "+f"(d[54]), "+f"(d[55]), "+f"(d[56]), "+f"(d[57]), "+f"(d[58]), "+f"(d[59]), "+f"(d[60]), "+f"(d[61]), "+f"(d[62]), "+f"(d[63]) : "l"(da), "l"(db), "r"(sd));
}
template<int SD> __device__ __forceinline__ void wgmma_rs_n64(float* d, const uint32_t* a, uint64_t db) {
  asm volatile("{.reg .pred p; setp.ne.b32 p, %37, 0; wgmma.mma_async.sync.aligned.m64n64k16.f32.bf16.bf16 {%0,%1,%2,%3,%4,%5,%6,%7,%8,%9,%10,%11,%12,%13,%14,%15,%16,%17,%18,%19,%20,%21,%22,%23,%24,%25,%26,%27,%28,%29,%30,%31}, {%32,%33,%34,%35}, %36, p, 1, 1, 0;}"
    : "+f"(d[0]), "+f"(d[1]), "+f"(d[2]), "+f"(d[3]), "+f"(d[4]), "+f"(d[5]), "+f"(d[6]), "+f"(d[7]), "+f"(d[8]), "+f"(d[9]), "+f"(d[10]), "+f"(d[11]), "+f"(d[12]), "+f"(d[13]), "+f"(d[14]), "+f"(d[15]), "+f"(d[16]), "+f"(d[17]), "+f"(d[18]), "+f"(d[19]), "+f"(d[20]), "+f"(d[21]), "+f"(d[22]), "+f"(d[23]), "+f"(d[24]), "+f"(d[25]), "+f"(d[26]), "+f"(d[27]), "+f"(d[28]), "+f"(d[29]), "+f"(d[30]), "+f"(d[31]) : "r"(a[0]), "r"(a[1]), "r"(a[2]), "r"(a[3]), "l"(db), "n"(SD));
}
template<int SD> __device__ __forceinline__ void wgmma_rs_n24(float* d, const uint32_t* a, uint64_t db) {
  asm volatile("{.reg .pred p; setp.ne.b32 p, %17, 0; wgmma.mma_async.sync.aligned.m64n24k16.f32.bf16.bf16 {%0,%1,%2,%3,%4,%5,%6,%7,%8,%9,%10,%11}, {%12,%13,%14,%15}, %16, p, 1, 1, 0;}"
    : "+f"(d[0]), "+f"(d[1]), "+f"(d[2]), "+f"(d[3]), "+f"(d[4]), "+f"(d[5]), "+f"(d[6]), "+f"(d[7]), "+f"(d[8]), "+f"(d[9]), "+f"(d[10]), "+f"(d[11]) : "r"(a[0]), "r"(a[1]), "r"(a[2]), "r"(a[3]), "l"(db), "n"(SD));
}
template<int SD> __device__ __forceinline__ void wgmma_rs_n32(float* d, const uint32_t* a, uint64_t db) {
  asm volatile("{.reg .pred p; setp.ne.b32 p, %21, 0; wgmma.mma_async.sync.aligned.m64n32k16.f32.bf16.bf16 {%0,%1,%2,%3,%4,%5,%6,%7,%8,%9,%10,%11,%12,%13,%14,%15}, {%16,%17,%18,%19}, %20, p, 1, 1, 0;}"
    : "+f"(d[0]), "+f"(d[1]), "+f"(d[2]), "+f"(d[3]), "+f"(d[4]), "+f"(d[5]), "+f"(d[6]), "+f"(d[7]), "+f"(d[8]), "+f"(d[9]), "+f"(d[10]), "+f"(d[11]), "+f"(d[12]), "+f"(d[13]), "+f"(d[14]), "+f"(d[15]) : "r"(a[0]), "r"(a[1]), "r"(a[2]), "r"(a[3]), "l"(db), "n"(SD));
}
template<int SD> __device__ __forceinline__ void wgmma_rs_n40(float* d, const uint32_t* a, uint64_t db) {
  asm volatile("{.reg .pred p; setp.ne.b32 p, %25, 0; wgmma.mma_async.sync.aligned.m64n40k16.f32.bf16.bf16 {%0,%1,%2,%3,%4,%5,%6,%7,%8,%9,%10,%11,%12,%13,%14,%15,%16,%17,%18,%19}, {%20,%21,%22,%23}, %24, p, 1, 1, 0;}"
    : "+f"(d[0]), "+f"(d[1]), "+f"(d[2]), "+f"(d[3]), "+f"(d[4]), "+f"(d[5]), "+f"(d[6]), "+f"(d[7]), "+f"(d[8]), "+f"(d[9]), "+f"(d[10]), "+f"(d[11]), "+f"(d[12]), "+f"(d[13]), "+f"(d[14]), "+f"(d[15]), "+f"(d[16]), "+f"(d[17]), "+f"(d[18]), "+f"(d[19]) : "r"(a[0]), "r"(a[1]), "r"(a[2]), "r"(a[3]), "l"(db), "n"(SD));
}
template<int SD> __device__ __forceinline__ void wgmma_rs_n24_tb(float* d, const uint32_t* a, uint64_t db) {
  asm volatile("{.reg .pred p; setp.ne.b32 p, %17, 0; wgmma.mma_async.sync.aligned.m64n24k16.f32.bf16.bf16 {%0,%1,%2,%3,%4,%5,%6,%7,%8,%9,%10,%11}, {%12,%13,%14,%15}, %16, p, 1, 1, 1;}"
    : "+f"(d[0]), "+f"(d[1]), "+f"(d[2]), "+f"(d[3]), "+f"(d[4]), "+f"(d[5]), "+f"(d[6]), "+f"(d[7]), "+f"(d[8]), "+f"(d[9]), "+f"(d[10]), "+f"(d[11]) : "r"(a[0]), "r"(a[1]), "r"(a[2]), "r"(a[3]), "l"(db), "n"(SD));
}

constexpr uint64_t DESC_SW128 = (uint64_t)1 << 62;
constexpr uint64_t DESC_SW32 = (uint64_t)3 << 62;
__device__ __forceinline__ uint64_t mk_desc(uint64_t sw, uint32_t addr, uint32_t lbo, uint32_t sbo) {
    return sw | ((uint64_t)(sbo >> 4) << 32) | ((uint64_t)(lbo >> 4) << 16) | (uint64_t)((addr & 0x3FFFF) >> 4);
}

constexpr uint32_t SM_BASE = 1024;
constexpr uint32_t P1_STAGE = 40960;
constexpr uint32_t P1_STGA = 98304;
constexpr uint32_t P1_RED = 147456;
constexpr uint32_t AT_Q = 0, AT_K = 16384, AT_V = 81920, AT_TAB = 163840, AT_ONES = 230400, AT_CT = 230912;
constexpr uint32_t P3_O = AT_TAB;
constexpr uint32_t BAR = 229376;
constexpr uint32_t B_FULL = BAR, B_EMPTY = BAR + 32;
constexpr uint32_t B_KV = BAR + 96, B_Q = BAR + 160, B_CONS = BAR + 168, B_WFULL = BAR + 232, B_OFULL = BAR + 296, B_OEMPTY = BAR + 328;
constexpr uint32_t B_STFREE = BAR + 360;
constexpr uint32_t OFF_MAX = BAR + 416, OFF_NORM = BAR + 512;
constexpr int SMEM_BYTES = BAR + 1024 + 832;
constexpr uint32_t B_TAB = BAR + 64;
constexpr float QSCALE = 0.25f * 1.4426950408889634f;

struct Maps { CUtensorMap xA, xB, wA, wB, o, o16, woA, woB, out; };

__device__ __forceinline__ void phase_qkv(uint8_t* smem, const Maps& mp) {
    constexpr uint32_t sb = SM_BASE;
    const int tid = threadIdx.x, warp = tid >> 5, lane = tid & 31;
    const int nt = blockIdx.x & 7, mt = blockIdx.x >> 3;
    float* sMax = (float*)(smem + OFF_MAX);
    auto produce = [&](int kb) {
        const int s = kb & 3;
        const uint32_t full = sb + B_FULL + 8 * s, st = sb + s * P1_STAGE;
        mbar_expect_tx(full, P1_STAGE);
        tma_load_2d(st, kb < 8 ? &mp.xB : &mp.xA, (kb & 7) * 64, mt * 128, full);
#pragma unroll
        for (int j = 0; j < 3; j++) tma_load_2d(st + 16384 + j * 8192, kb < 8 ? &mp.wB : &mp.wA, j * 512 + nt * 64, (kb & 7) * 64, full);
    };
    if (tid == 0) {
        tma_prefetch_desc(&mp.xB); tma_prefetch_desc(&mp.wB);
        for (int i = 0; i < 4; i++) { mbar_init(sb + B_FULL + 8 * i, 1); mbar_init(sb + B_EMPTY + 8 * i, 2); }
        fence_mbar_init();
        DSTAMP(28);
        for (int kb = 0; kb < 4; kb++) produce(kb);
        DSTAMP(29);
        tma_prefetch_desc(&mp.xA); tma_prefetch_desc(&mp.wA);
    }
    if (tid == 32) {
                for (int i = 0; i < 4; i++) mbar_init(sb + B_STFREE + 8 * i, 2);
        mbar_init(sb + B_Q, 1); mbar_init(sb + B_TAB, 256);
        for (int i = 0; i < 8; i++) { mbar_init(sb + B_KV + 8 * i, 1); mbar_init(sb + B_CONS + 8 * i, 4); mbar_init(sb + B_WFULL + 8 * i, 1); }
        for (int i = 0; i < 4; i++) { mbar_init(sb + B_OFULL + 8 * i, 1); mbar_init(sb + B_OEMPTY + 8 * i, 2); }
        fence_mbar_init();
    }
    if (tid >= 64 && tid < 72) sMax[tid - 64] = 0.f;
    __syncthreads();
    STAMP(0, 1);

    const int wg = __shfl_sync(0xffffffffu, warp >> 2, 0);
    const int branchB = wg < 2;
    const int wh = wg & 1;
    const int kb0 = branchB ? 0 : 8;
    float acc[96];
#pragma unroll
    for (int i = 0; i < 96; i++) acc[i] = 0.f;
    fence_regs(acc);
    if (!branchB) {
        const int w = warp & 7, j = w * 32 + lane;
        const float f = (j + 0.5f) * (1.f / 256.f);
        const uint32_t val = (uint32_t)(__float2int_rn((exp2f(f) - 1.f) * 128.f) - (j >> 1) + (63 << 7) - 0x8000);
        uint4* tb = (uint4*)(smem + AT_TAB) + w * 32 * 8 + lane;
#pragma unroll
        for (int i = 0; i < 8; i++) {
            const uint32_t v = __shfl_sync(0xffffffffu, val, i * 4 + (lane >> 3));
            tb[i * 32] = make_uint4(v, v, v, v);
            tb[2048 + i * 32] = make_uint4(v << 16, v << 16, v << 16, v << 16);
        }
        if (w == 0) { for (int i = lane; i < 128; i += 32) ((uint32_t*)(smem + AT_ONES))[i] = 0x3F803F80u; }
        if (w == 1) {
            for (int i = lane; i < 64; i += 32) {
                const int r = i >> 3, ww = i & 7, chunk = (ww >> 2) ^ (r >> 2);
                ((uint32_t*)(smem + AT_CT))[i] = (chunk == 0 && (ww & 3) == 0) ? 0x000043A0u : 0u;
            }
        }
        if (w == 2 && lane < 8) ((uint32_t*)(smem + AT_CT + 256))[lane] = lane < 2 ? 0x00003F80u : 0u;
        fence_async_smem();
        mbar_arrive(sb + B_TAB);
        named_bar(3, 512);
    }
    const uint64_t dA0 = mk_desc(DESC_SW128, sb + wh * 8192, 16, 1024);
#pragma unroll
    for (int i = 0; i < 8; i++) {
        const int kb = kb0 + i, s = i & 3;
        mbar_wait(sb + B_FULL + 8 * s, (i >> 2) & 1);
        if (kb == 0) STAMP(0, 2);
        if ((tid & 255) == 0) DSTAMP(kb);
        const uint64_t dA = dA0 + (uint64_t)(s * (P1_STAGE >> 4)), dB = mk_desc(DESC_SW128, sb + s * P1_STAGE + 16384, 8192, 1024);
        wg_fence();
#pragma unroll
        for (int k = 0; k < 4; k++) wgmma_ss_n192_tb(acc, dA + k * 2, dB + k * 128, 1);
        wg_commit();
        if (i == 7 && branchB) asm volatile("bar.arrive 3, 512;" ::: "memory");
        if (i > 0) {
            wg_wait<1>();
            if (i >= 5 && !branchB && (tid & 127) == 0) mbar_arrive(sb + B_STFREE + 8 * (i - 5));
            if (kb + 3 < 16) {
                const uint32_t eb = sb + B_EMPTY + 8 * ((i - 1) & 3);
                if ((tid & 127) == 0) {
                    mbar_arrive(eb);
                    if (wh == 0) { mbar_wait(eb, ((i - 1) >> 2) & 1); produce(kb + 3); }
                }
                __syncwarp();
            }
        }
    }
    wg_wait<0>();
    fence_regs(acc);
    STAMP(0, 3);

    const int wq = warp & 3, g = lane >> 2, t = lane & 3;
    const int lr = (lane & 7) + ((lane >> 3) & 1) * 8;
    const int lc = lane >> 4;
    const int row0 = mt * 128;
    const int w8 = warp & 7;
    if (branchB) {
        {
            const uint32_t eb = sb + B_EMPTY + 8 * 3;
            if ((tid & 127) == 0) {
                mbar_arrive(eb);
                if (wh == 0) { mbar_wait(eb, 1); produce(11); }
            }
            __syncwarp();
        }
        const int orow = g + (t >> 1) * 8;
        const uint32_t ooff = (uint32_t)(row0 + wh * 64 + wq * 16 + orow) * 32 + (((t & 1) ^ ((orow & 7) >> 2)) << 4);
        const bool o1 = t & 1, o2 = t & 2;
        uint32_t mymax = 0;
#pragma unroll
        for (int sl = 0; sl < 12; sl++) {
            float* a = acc + sl * 8;
            if (sl < 4) {
#pragma unroll
                for (int i = 0; i < 8; i++) a[i] *= QSCALE;
            }
            if (sl < 8) {
                const float n0 = fmaf(a[0], a[0], fmaf(a[1], a[1], fmaf(a[4], a[4], a[5] * a[5])));
                const float n1 = fmaf(a[2], a[2], fmaf(a[3], a[3], fmaf(a[6], a[6], a[7] * a[7])));
                const uint32_t m = __reduce_max_sync(0xffffffffu, __float_as_uint(fmaxf(n0, n1)));
                if (lane == sl) mymax = m;
            }
            const uint32_t w0 = pack_bf16(a[0], a[1]), w2 = pack_bf16(a[2], a[3]), w1 = pack_bf16(a[4], a[5]), w3 = pack_bf16(a[6], a[7]);
            const uint32_t r0 = __shfl_xor_sync(0xffffffffu, o1 ? w0 : w1, 1), r1 = __shfl_xor_sync(0xffffffffu, o1 ? w2 : w3, 1);
            const uint32_t x0 = o1 ? r0 : w0, x1 = o1 ? w1 : r0, y0 = o1 ? r1 : w2, y1 = o1 ? w3 : r1;
            const uint32_t q0 = __shfl_xor_sync(0xffffffffu, o2 ? x0 : y0, 2), q1 = __shfl_xor_sync(0xffffffffu, o2 ? x1 : y1, 2);
            uint4 val;
            val.x = o2 ? q0 : x0; val.y = o2 ? q1 : x1; val.z = o2 ? y0 : q0; val.w = o2 ? y1 : q1;
            const int ty = sl >> 2, head = nt * 4 + (sl & 3);
            uint8_t* dst = (uint8_t*)((ty == 0 ? g_qB : (ty == 1 ? g_kB : g_vB)) + (size_t)head * S_LEN * 16);
            *(uint4*)(dst + ooff) = val;
        }
        if (lane < 8) atomicMax((unsigned int*)&sMax[lane], mymax);
        named_bar(1, 256);
        if (tid == 0) DSTAMP(16);
        if (w8 == 7 && lane >= 8 && lane < 16) { const int i = lane - 8; (i < 4 ? g_qn : g_kn)[(nt * 4 + (i & 3)) * 16 + mt] = sMax[i]; }
        named_bar(1, 256);
        const int h = blockIdx.x >> 2, qb = blockIdx.x & 3;
        if (tid == 0) signal_add(&g_cnt.qkvB[nt]);
        auto ld_k = [&](int c) {
            mbar_expect_tx(sb + B_KV + 8 * c, 16384);
            bulk_g2s(sb + AT_K + c * 8192, g_kB + ((size_t)h * S_LEN + c * 256) * 16, 8192, sb + B_KV + 8 * c);
        };
        auto ld_v = [&](int c) { bulk_g2s(sb + AT_V + c * 8192, g_vB + ((size_t)h * S_LEN + c * 256) * 16, 8192, sb + B_KV + 8 * c); };
        if (tid == 32) {
            spin_ge(&g_cnt.qkvB[h >> 2], 16);
            fence_async_all();
            mbar_wait(sb + B_STFREE, 0);
            mbar_expect_tx(sb + B_Q, 16384 + 128);
            bulk_g2s(sb + AT_Q, g_qB + ((size_t)h * S_LEN + qb * 512) * 16, 16384, sb + B_Q);
            ld_k(0);
            bulk_g2s(sb + OFF_NORM, g_qn + h * 16, 64, sb + B_Q);
            bulk_g2s(sb + OFF_NORM + 64, g_kn + h * 16, 64, sb + B_Q);
            DSTAMP(27);
            mbar_wait(sb + B_STFREE + 16, 0);
            ld_v(0); ld_k(1); ld_v(1);
        }
        __syncwarp();
        STAMP(0, 5);
    } else {
        if ((tid & 127) == 0) mbar_arrive(sb + B_STFREE + 8 * 3);
        if (tid == 256) DSTAMP(22);
        named_bar(2, 256);
        const uint32_t stg = sb + P1_STGA;
        const uint32_t stAddr = stg + (wh * 64 + wq * 16 + lr) * 32 + (((lc ^ ((lr & 7) >> 2))) << 4);
#pragma unroll
        for (int sl = 0; sl < 12; sl++) {
            float* a = acc + sl * 8;
            uint32_t p0 = pack_bf16(a[0], a[1]), p1 = pack_bf16(a[2], a[3]), p2 = pack_bf16(a[4], a[5]), p3 = pack_bf16(a[6], a[7]);
            if (sl >= 4 && sl < 8) { p0 = phi_bf16x2(p0); p1 = phi_bf16x2(p1); p2 = phi_bf16x2(p2); p3 = phi_bf16x2(p3); }
            stsm_x4(stAddr + sl * 4096, p0, p1, p2, p3);
        }
        named_bar(2, 256);
        if (tid == 256) DSTAMP(23);
#pragma unroll
        for (int sl = 0; sl < 4; sl++)
            *(uint4*)((uint8_t*)(g_qA + ((size_t)(nt * 4 + sl) * S_LEN + row0) * 16) + (tid - 256) * 16) = *(const uint4*)(smem + P1_STGA + sl * 4096 + (tid - 256) * 16);
        const int hh = w8 & 3;
        const uint32_t pkb = stg + (4 + hh) * 4096 + wh * 2048, vb = stg + (8 + hh) * 4096 + wh * 2048;
        float kv0[4] = {0.f, 0.f, 0.f, 0.f}, kv1[4] = {0.f, 0.f, 0.f, 0.f}, zz[4] = {0.f, 0.f, 0.f, 0.f};
        const int ar = (lane & 7) + (lane >> 4) * 8, ac = (lane >> 3) & 1;
        const int br = (lane & 7) + ((lane >> 3) & 1) * 8, bc = lane >> 4;
#pragma unroll
        for (int ks = 0; ks < 4; ks++) {
            uint32_t af[4], bf[4];
            ldsm_x4_t(pkb + (ks * 16 + ar) * 32 + ((ac ^ ((ar & 7) >> 2)) << 4), af);
            ldsm_x4_t(vb + (ks * 16 + br) * 32 + ((bc ^ ((br & 7) >> 2)) << 4), bf);
            mma_bf16(kv0, af, bf[0], bf[1]);
            mma_bf16(kv1, af, bf[2], bf[3]);
            mma_bf16(zz, af, 0x3F803F80u, 0x3F803F80u);
        }
        if (tid == 256) DSTAMP(24);
        float* rp = (float*)(smem + P1_RED) + hh * 272;
        if (wh == 1) {
            rp[g * 16 + 2 * t] = kv0[0]; rp[g * 16 + 2 * t + 1] = kv0[1];
            rp[(g + 8) * 16 + 2 * t] = kv0[2]; rp[(g + 8) * 16 + 2 * t + 1] = kv0[3];
            rp[g * 16 + 8 + 2 * t] = kv1[0]; rp[g * 16 + 8 + 2 * t + 1] = kv1[1];
            rp[(g + 8) * 16 + 8 + 2 * t] = kv1[2]; rp[(g + 8) * 16 + 8 + 2 * t + 1] = kv1[3];
            if (t == 0) { rp[256 + g] = zz[0]; rp[256 + g + 8] = zz[2]; }
        }
        named_bar(2, 256);
        if (wh == 0) {
            float* gp = g_kvp + (size_t)(mt * NH + nt * 4 + hh) * 272;
            *(float2*)(gp + g * 16 + 2 * t) = make_float2(kv0[0] + rp[g * 16 + 2 * t], kv0[1] + rp[g * 16 + 2 * t + 1]);
            *(float2*)(gp + (g + 8) * 16 + 2 * t) = make_float2(kv0[2] + rp[(g + 8) * 16 + 2 * t], kv0[3] + rp[(g + 8) * 16 + 2 * t + 1]);
            *(float2*)(gp + g * 16 + 8 + 2 * t) = make_float2(kv1[0] + rp[g * 16 + 8 + 2 * t], kv1[1] + rp[g * 16 + 8 + 2 * t + 1]);
            *(float2*)(gp + (g + 8) * 16 + 8 + 2 * t) = make_float2(kv1[2] + rp[(g + 8) * 16 + 8 + 2 * t], kv1[3] + rp[(g + 8) * 16 + 8 + 2 * t + 1]);
            if (t == 0) { gp[256 + g] = zz[0] + rp[256 + g]; gp[256 + g + 8] = zz[2] + rp[256 + g + 8]; }
        }
        STAMP(0, 6);
    }
}

constexpr int AT_NT = 64;
#define AT_NP_V 32
#define AT_NP2_V 40
constexpr int AT_NP = AT_NP_V, AT_NP2 = AT_NP2_V;
constexpr float AT_SAFE2 = 56.f * 56.f;

__device__ __forceinline__ uint32_t ex2_tab2(float ya, float yb, uint32_t lane4) {
    const uint32_t a = __float_as_uint(ya), b = __float_as_uint(yb);
    uint32_t aa, ab, ta, tb, L;
    asm("lop3.b32 %0, %1, 0x7F80, %2, 0xEA;" : "=r"(aa) : "r"(a), "r"(lane4));
    asm("lop3.b32 %0, %1, 0x7F80, %2, 0xEA;" : "=r"(ab) : "r"(b), "r"(lane4));
    asm volatile("ld.shared.u32 %0, [%1+%2];" : "=r"(ta) : "r"(aa), "n"(SM_BASE + AT_TAB));
    asm volatile("ld.shared.u32 %0, [%1+%2];" : "=r"(tb) : "r"(ab), "n"(SM_BASE + AT_TAB + 32768));
    asm("prmt.b32 %0, %1, %2, 0x6521;" : "=r"(L) : "r"(a), "r"(b));
    return L + ta + tb;
}
template <int NT, int NP>
__device__ __forceinline__ void att_exp(const float* s, uint32_t* p, uint32_t lane4) {
    constexpr int PP = NP / 4, TOT = NT / 4;
#pragma unroll
    for (int i = 0; i < TOT; i++) {
        const int nb = (i * PP) / TOT, na = ((i + 1) * PP) / TOT;
        if (na != nb) p[nb] = ex2_tab2(s[2 * nb], s[2 * nb + 1], lane4);
        else { const int im = PP + i - nb; p[im] = pack_bf16(ex2f(s[2 * im]), ex2f(s[2 * im + 1])); }
    }
}

__device__ __forceinline__ void mbar_arrive_elect(uint32_t bar) {
    asm volatile("{.reg .pred p;\nelect.sync _|p, 0xffffffff;\n@p mbarrier.arrive.shared::cta.b64 _, [%0];\n}" ::"r"(bar) : "memory");
}
__device__ __forceinline__ void load_wo_elect(const Maps& mp, int branchB, int nt, int c) {
    constexpr uint32_t sb = SM_BASE;
    const CUtensorMap* tm = branchB ? &mp.woB : &mp.woA;
    asm volatile(
        "{.reg .pred p;\n"
        "elect.sync _|p, 0xffffffff;\n"
        "@p mbarrier.arrive.expect_tx.shared::cta.b64 _, [%0], 16384;\n"
        "@p cp.async.bulk.tensor.2d.shared::cluster.global.mbarrier::complete_tx::bytes [%1], [%3, {%4, %6}], [%0];\n"
        "@p cp.async.bulk.tensor.2d.shared::cluster.global.mbarrier::complete_tx::bytes [%2], [%3, {%5, %6}], [%0];\n"
        "}" ::"r"(sb + B_WFULL + 8 * c), "r"(sb + AT_K + c * 8192), "r"(sb + AT_V + c * 8192), "l"(tm), "r"(nt * 128), "r"(nt * 128 + 64), "r"(c * 64)
        : "memory");
}
__device__ __forceinline__ void load_kv_elect(int h, int c) {
    constexpr uint32_t sb = SM_BASE;
    asm volatile(
        "{.reg .pred p;\n"
        "elect.sync _|p, 0xffffffff;\n"
        "@p mbarrier.arrive.expect_tx.shared::cta.b64 _, [%0], 16384;\n"
        "@p cp.async.bulk.shared::cluster.global.mbarrier::complete_tx::bytes [%1], [%3], 8192, [%0];\n"
        "@p cp.async.bulk.shared::cluster.global.mbarrier::complete_tx::bytes [%2], [%4], 8192, [%0];\n"
        "}" ::"r"(sb + B_KV + 8 * c), "r"(sb + AT_K + c * 8192), "r"(sb + AT_V + c * 8192),
        "l"(g_kB + ((size_t)h * S_LEN + c * 256) * 16), "l"(g_vB + ((size_t)h * S_LEN + c * 256) * 16) : "memory");
}
__device__ __forceinline__ void load_wo(const Maps& mp, int branchB, int nt, int c) {
    constexpr uint32_t sb = SM_BASE;
    const CUtensorMap* tm = branchB ? &mp.woB : &mp.woA;
    mbar_expect_tx(sb + B_WFULL + 8 * c, 16384);
    tma_load_2d(sb + AT_K + c * 8192, tm, nt * 128, c * 64, sb + B_WFULL + 8 * c);
    tma_load_2d(sb + AT_V + c * 8192, tm, nt * 128 + 64, c * 64, sb + B_WFULL + 8 * c);
}

__device__ __forceinline__ void phase_attn(uint8_t* smem, const Maps& mp) {
    constexpr uint32_t sb = SM_BASE;
    const int tid = threadIdx.x, warp = (tid >> 5) & 3, lane = tid & 31;
    const int wg = __shfl_sync(0xffffffffu, tid >> 7, 0);
    const int wwarp = __shfl_sync(0xffffffffu, warp, 0);
    const int h = blockIdx.x >> 2, qb = blockIdx.x & 3;
    constexpr int NCH = 8;
    constexpr uint32_t sK = sb + AT_K, sV = sb + AT_V, sQ = sb + AT_Q, sBar = sb + B_KV;

    named_bar(4 + wg, 128);
    mbar_wait(sb + B_TAB, 0);
    mbar_wait(sb + B_Q, 0);
    if (wg >= 2) {
        named_bar(2, 256);
        if (wwarp < 3) load_kv_elect(h, 2 + (wg - 2) * 3 + wwarp);
    }
    __syncwarp();
    STAMP(1, 2);
    bool safe;
    {
        const float* nrm = (const float*)(smem + OFF_NORM);
        const float qv = lane < 4 ? nrm[qb * 4 + lane] : 0.f;
        const float kv = lane < 16 ? nrm[16 + lane] : 0.f;
        const uint32_t qm = __reduce_max_sync(0xffffffffu, __float_as_uint(qv));
        const uint32_t km = __reduce_max_sync(0xffffffffu, __float_as_uint(kv));
        safe = (__uint_as_float(qm) * __uint_as_float(km) * (16.f * 1.05f) < AT_SAFE2);
    }
    const uint64_t dK0 = mk_desc(DESC_SW32, sK, 16, 256);
    const uint64_t dC = mk_desc(DESC_SW32, sb + AT_CT, 16, 0);
    const uint64_t dV0 = mk_desc(DESC_SW32, sV, AT_ONES - AT_V, 256);
    constexpr int64_t VSTEP = 32 - (32 << 16);
    const uint32_t lane4 = lane * 4;
    uint32_t aone[4];
    asm volatile("ld.shared.v4.u32 {%0,%1,%2,%3}, [%4];" : "=r"(aone[0]), "=r"(aone[1]), "=r"(aone[2]), "=r"(aone[3]) : "r"(sb + AT_CT + 256 + ((lane & 3) == 0 ? 0 : 16)));
    const int g = lane >> 2, t = lane & 3;
    constexpr int NT = AT_NT, NP = AT_NP;
    const int oBranch = blockIdx.x >> 6, oNt = blockIdx.x & 3;

    STAMP(1, 3);
#pragma unroll 1
    for (int qi = 0; qi < 2; qi++) {
        const int qt = wg * 2 + qi;
        const int row0 = qb * 512 + qt * 64 + warp * 16;
        uint32_t qa[4];
        ldsm_x4(sQ + (qt * 64 + warp * 16 + (lane & 7) + ((lane >> 3) & 1) * 8) * 32 + ((((lane >> 4) ^ ((lane & 7) >> 2))) << 4), qa);
        float o[12], s[NT / 2];
#pragma unroll
        for (int i = 0; i < 12; i++) o[i] = 0.f;
#pragma unroll
        for (int i = 0; i < NT / 2; i++) s[i] = 0.f;
        fence_regs(o); fence_regs(s);
        if (safe) {
            uint32_t pa[NT / 4], pb[NT / 4];
            auto issue_qk = [&](uint64_t dK, int np) {
                wgmma_rs_n64<0>(s, qa, dK);
                if (np == 24) wgmma_rs_n24<1>(s, aone, dC); else if (np == 32) wgmma_rs_n32<1>(s, aone, dC); else wgmma_rs_n40<1>(s, aone, dC);
            };
            mbar_wait(sBar, 0);
            wg_fence();
            issue_qk(dK0, NP);
            wg_commit();
            wg_wait<0>();
            fence_regs(s);
            att_exp<NT, NP>(s, pa, lane4);
            uint64_t dK = dK0, dV = dV0;
            auto step = [&](uint32_t (&pc)[NT / 4], uint32_t (&pn)[NT / 4], bool last, int jt) {
                wg_fence();
                if (!last) { issue_qk(dK + (uint64_t)(jt * NT * 2 + NT * 2), (jt & 1) ? NP : AT_NP2); wg_commit(); }
#pragma unroll
                for (int kk = 0; kk < NT / 16; kk++) wgmma_rs_n24_tb<1>(o, pc + kk * 4, dV + (uint64_t)((int64_t)(jt * (NT / 16) + kk) * VSTEP));
                wg_commit();
                if (!last) {
                    wg_wait<1>();
                    fence_regs(s);
                    if (jt & 1) att_exp<NT, NP>(s, pn, lane4); else att_exp<NT, AT_NP2>(s, pn, lane4);
                }
                if (last || jt == 3) { wg_wait<0>(); fence_regs(pc); fence_regs(o); }
            };
            constexpr int TPC = 256 / NT;
#pragma unroll 1
            for (int cch = 0; cch < NCH; cch++) {
#pragma unroll
                for (int jj = 0; jj < TPC; jj += 2) {
                    step(pa, pb, false, jj);
                    if (jj + 2 == TPC) {
                        if (cch == NCH - 1) break;
                        mbar_wait(sBar + 8 * (cch + 1), 0);
                    }
                    step(pb, pa, false, jj + 1);
                    if (jj == 0 && qi == 0 && cch == 0 && wg == 2 && wwarp == 0) {
                        asm volatile("{.reg .pred p;\nelect.sync _|p, 0xffffffff;\n@p red.release.gpu.global.add.s32 [%0], 1;\n}" ::"l"(&g_cnt.qkvA[blockIdx.x & 7]) : "memory");
                    }
                }
                dK += 256 * 2; dV += (uint64_t)(16 * VSTEP);
                if (qi == 1 && wwarp == 0 && cch < NCH - 1) {
                    mbar_arrive_elect(sb + B_CONS + 8 * cch);
                    if (cch >= 1 && wg == ((cch - 1) & 3)) { mbar_wait(sb + B_CONS + 8 * (cch - 1), 0); load_wo_elect(mp, oBranch, oNt, cch - 1); }
                }
            }
            dV -= (uint64_t)(16 * VSTEP);
            step(pb, pa, true, TPC - 1);
            if (qi == 1 && wwarp == 0) {
                mbar_arrive_elect(sb + B_CONS + 8 * 7);
                if (wg == 2) { mbar_wait(sb + B_CONS + 8 * 6, 0); load_wo_elect(mp, oBranch, oNt, 6); }
                if (wg == 3) { mbar_wait(sb + B_CONS + 8 * 7, 0); load_wo_elect(mp, oBranch, oNt, 7); }
            }
        } else {
            if (qi == 0 && tid == 256) signal_add(&g_cnt.qkvA[blockIdx.x & 7]);
            float m0 = -INFINITY, m1 = -INFINITY;
            uint32_t p[NT / 4];
#pragma unroll 1
            for (int j = 0; j < S_LEN / NT; j++) {
                if ((j * NT) % 256 == 0) mbar_wait(sBar + 8 * ((j * NT) / 256), 0);
                wg_fence();
                wgmma_rs_n64<0>(s, qa, dK0 + (uint64_t)(j * NT * 2));
                wg_commit();
                wg_wait<0>();
                fence_regs(s); fence_regs(o);
                float t0 = m0, t1 = m1;
#pragma unroll
                for (int i = 0; i < NT / 2; i += 4) { t0 = fmaxf(t0, fmaxf(s[i], s[i + 1])); t1 = fmaxf(t1, fmaxf(s[i + 2], s[i + 3])); }
                t0 = fmaxf(t0, __shfl_xor_sync(0xffffffffu, t0, 1)); t0 = fmaxf(t0, __shfl_xor_sync(0xffffffffu, t0, 2));
                t1 = fmaxf(t1, __shfl_xor_sync(0xffffffffu, t1, 1)); t1 = fmaxf(t1, __shfl_xor_sync(0xffffffffu, t1, 2));
                const float r0 = ex2f(m0 - t0), r1 = ex2f(m1 - t1);
                m0 = t0; m1 = t1;
#pragma unroll
                for (int i = 0; i < 12; i += 4) { o[i] *= r0; o[i + 1] *= r0; o[i + 2] *= r1; o[i + 3] *= r1; }
#pragma unroll
                for (int i = 0; i < NT / 4; i += 2) {
                    p[i] = pack_bf16(ex2f(s[2 * i] - m0), ex2f(s[2 * i + 1] - m0));
                    p[i + 1] = pack_bf16(ex2f(s[2 * i + 2] - m1), ex2f(s[2 * i + 3] - m1));
                }
                fence_regs(o);
                wg_fence();
#pragma unroll
                for (int kk = 0; kk < NT / 16; kk++) wgmma_rs_n24_tb<1>(o, p + kk * 4, dV0 + (uint64_t)((int64_t)(j * (NT / 16) + kk) * VSTEP));
                wg_commit();
                wg_wait<0>();
                fence_regs(p);
            }
            fence_regs(o);
        }
        const float l0 = 1.f / o[8], l1 = 1.f / o[10];
        uint32_t* op0 = (uint32_t*)(g_o + (size_t)(row0 + g) * 1024 + 512 + h * 16);
        uint32_t* op1 = (uint32_t*)(g_o + (size_t)(row0 + g + 8) * 1024 + 512 + h * 16);
        op0[t] = pack_bf16(o[0] * l0, o[1] * l0);
        op0[4 + t] = pack_bf16(o[4] * l0, o[5] * l0);
        op1[t] = pack_bf16(o[2] * l1, o[3] * l1);
        op1[4 + t] = pack_bf16(o[6] * l1, o[7] * l1);
    }
    named_bar(4 + wg, 128);
    if ((tid & 127) == 0) signal_add(&g_cnt.oB[(qb * 4 + wg) * 8 + (h >> 2)]);
    STAMP(1, 4);
    __syncthreads();
    if (!safe && tid == 0) {
        for (int c = 0; c < 8; c++) load_wo(mp, oBranch, oNt, c);
    }
}

__device__ __forceinline__ void phase_out(uint8_t* smem, const Maps& mp) {
    (void)smem;
    constexpr uint32_t sb = SM_BASE;
    const int tid = threadIdx.x, warp = tid >> 5, lane = tid & 31;
    const int branchB = blockIdx.x >> 6;
    const int mt = (blockIdx.x & 63) >> 2, nt = blockIdx.x & 3;
    const int wg = __shfl_sync(0xffffffffu, warp >> 2, 0);
    if (wg == 2) {
        if (tid < 256 + 32) {
            if (lane == 0) { tma_prefetch_desc(&mp.o); tma_prefetch_desc(&mp.out); }
            const int* cnt = branchB ? &g_cnt.oB[mt * 8 + (lane & 7)] : &g_cnt.oA;
            int next = 0, spins = 0;
            while (next < 8) {
                int v;
                asm volatile("ld.acquire.gpu.global.s32 %0, [%1];" : "=r"(v) : "l"(cnt) : "memory");
                const uint32_t ready = __ballot_sync(0xffffffffu, v >= 4);
                __syncwarp();
                if (lane == 0) {
                    fence_async_all();
                    for (int kb = next; kb < 8 && ((ready >> kb) & 1); kb++) {
                        const int s = kb & 3;
                        if (kb >= 4) mbar_wait(sb + B_OEMPTY + 8 * s, 0);
                        mbar_expect_tx(sb + B_OFULL + 8 * s, 16384);
                        tma_load_2d(sb + P3_O + s * 16384, &mp.o, branchB * 512 + kb * 64, mt * 128, sb + B_OFULL + 8 * s);
                    }
                }
                while (next < 8 && ((ready >> next) & 1)) next++;
                __syncwarp();
                if (++spins > (1 << 22)) __trap();
                if (next < 8) __nanosleep(SPIN_NS);
            }
            if (lane == 0) finish_ticket();
        }
        return;
    }
    if (wg == 3) return;
    float acc[64];
#pragma unroll
    for (int i = 0; i < 64; i++) acc[i] = 0.f;
    fence_regs(acc);
    const uint64_t dA0 = mk_desc(DESC_SW128, sb + P3_O + wg * 8192, 16, 1024);
#pragma unroll
    for (int kb = 0; kb < 8; kb++) {
        const int s = kb & 3;
        mbar_wait(sb + B_WFULL + 8 * kb, 0);
        mbar_wait(sb + B_OFULL + 8 * s, kb >> 2);
        if (kb == 0) STAMP(2, 2);
        const uint64_t dA = dA0 + (uint64_t)(s * (16384 >> 4));
        const uint64_t dB = mk_desc(DESC_SW128, sb + AT_K + kb * 8192, AT_V - AT_K, 1024);
        wg_fence();
#pragma unroll
        for (int k = 0; k < 4; k++) wgmma_ss_n128_tb(acc, dA + k * 2, dB + k * 128, 1);
        wg_commit();
        if (kb >= 1 && kb <= 4) {
            wg_wait<1>();
            if ((tid & 127) == 0) mbar_arrive(sb + B_OEMPTY + 8 * (kb - 1));
        }
    }
    wg_wait<0>();
    fence_regs(acc);
    STAMP(2, 3);
    const int wq = warp & 3;
    const uint32_t stg = sb + P3_O + wg * 8192;
    const int lr = wq * 16 + (lane & 7) + ((lane >> 3) & 1) * 8, lc = lane >> 4;
#pragma unroll
    for (int j = 0; j < 8; j++) {
        const float* a = acc + j * 8;
        const int chunk = (j & 3) * 2 + lc;
        stsm_x4(stg + (j >> 2) * 16384 + lr * 128 + ((chunk ^ (lr & 7)) << 4),
                pack_bf16(a[0], a[1]), pack_bf16(a[2], a[3]), pack_bf16(a[4], a[5]), pack_bf16(a[6], a[7]));
    }
    fence_async_smem();
    named_bar(4 + wg, 128);
    if ((tid & 127) < 2) {
        const int j = tid & 1;
        tma_store_2d(&mp.out, stg + j * 16384, branchB * 512 + nt * 128 + j * 64, mt * 128 + wg * 64);
        bulk_commit();
        asm volatile("cp.async.bulk.wait_group.read 0;" ::: "memory");
    }
    STAMP(2, 4);
}

__device__ __noinline__ void linattn_mid(uint8_t* smem, int cta, const CUtensorMap* tmO16) {
    constexpr uint32_t sb = SM_BASE;
    const int tid = threadIdx.x, warp = tid >> 5, lane = tid & 31;
    constexpr int NBUF = 4;
    const uint32_t sBar = sb;
    const uint32_t sQ0 = sb + 1024;
    const uint32_t sSt = sQ0 + NBUF * 32768;
    float* skv = (float*)(smem + 1024 + NBUF * 32768 + 65536);
    if (tid == 0) { for (int i = 0; i < NBUF; i++) { mbar_init(sBar + 8 * i, 1); mbar_init(sBar + 64 + 8 * i, 16); } fence_mbar_init(); }
    __syncthreads();
    if (warp == 0 && lane == 0) { spin_ge(&g_cnt.qkvA[2 * cta], 16); spin_ge(&g_cnt.qkvA[2 * cta + 1], 16); finish_ticket(); }
    __syncthreads();
    if (lane == 0) fence_async_all();
    __syncwarp();
    STAMP(1, 2);
    auto load_chunk = [&](int c, int j) {
        bulk_g2s(sQ0 + (c % NBUF) * 32768 + j * 8192, g_qA + ((size_t)(cta * 8 + (c >> 3) * 4 + j) * S_LEN + (c & 7) * 256) * 16, 8192, sBar + 8 * (c % NBUF));
    };
    if (lane == 0 && warp < NBUF) {
        mbar_expect_tx(sBar + 8 * warp, 32768);
        for (int j = 0; j < 4; j++) load_chunk(warp, j);
    }
    for (int i = tid; i < 8 * 68; i += 512) {
        const int hh = i / 68, e = i - hh * 68;
        const float* gp = g_kvp + (size_t)(cta * 8 + hh) * 272 + e * 4;
        float4 v0, v1, v2, v3, v4, v5, v6, v7;
#define LD4(m) (*(const float4*)(gp + (size_t)(m) * NH * 272))
#define ADD4(a, b) (a).x += (b).x, (a).y += (b).y, (a).z += (b).z, (a).w += (b).w
        v0 = LD4(0); v1 = LD4(1); v2 = LD4(2); v3 = LD4(3); v4 = LD4(4); v5 = LD4(5); v6 = LD4(6); v7 = LD4(7);
        {
            const float4 w0 = LD4(8), w1 = LD4(9), w2 = LD4(10), w3 = LD4(11), w4 = LD4(12), w5 = LD4(13), w6 = LD4(14), w7 = LD4(15);
            ADD4(v0, w0); ADD4(v1, w1); ADD4(v2, w2); ADD4(v3, w3); ADD4(v4, w4); ADD4(v5, w5); ADD4(v6, w6); ADD4(v7, w7);
        }
        ADD4(v0, v4); ADD4(v1, v5); ADD4(v2, v6); ADD4(v3, v7); ADD4(v0, v2); ADD4(v1, v3); ADD4(v0, v1);
#undef LD4
#undef ADD4
        *(float4*)(skv + i * 4) = v0;
    }
    __syncthreads();
    STAMP(1, 3);
    const int g = lane >> 2, t = lane & 3;
    const int lr = (lane & 7) + ((lane >> 3) & 1) * 8, lc = lane >> 4;
    const uint32_t loff = (warp * 16 + lr) * 32 + ((lc ^ ((lr & 7) >> 2)) << 4);
#pragma unroll 1
    for (int quad = 0; quad < 2; quad++) {
        uint32_t bf[4][6];
#pragma unroll
        for (int j = 0; j < 4; j++) {
            const float* kv = skv + (quad * 4 + j) * 272;
            bf[j][0] = pack_bf16(kv[(2 * t) * 16 + g], kv[(2 * t + 1) * 16 + g]);
            bf[j][1] = pack_bf16(kv[(2 * t + 8) * 16 + g], kv[(2 * t + 9) * 16 + g]);
            bf[j][2] = pack_bf16(kv[(2 * t) * 16 + 8 + g], kv[(2 * t + 1) * 16 + 8 + g]);
            bf[j][3] = pack_bf16(kv[(2 * t + 8) * 16 + 8 + g], kv[(2 * t + 9) * 16 + 8 + g]);
            bf[j][4] = pack_bf16(kv[256 + 2 * t], kv[256 + 2 * t + 1]);
            bf[j][5] = pack_bf16(kv[256 + 2 * t + 8], kv[256 + 2 * t + 9]);
        }
#pragma unroll 1
        for (int rc = 0; rc < 8; rc++) {
            const int c = quad * 8 + rc;
            mbar_wait(sBar + 8 * (c % NBUF), (c / NBUF) & 1);
            const uint32_t qb = sQ0 + (c % NBUF) * 32768 + loff;
            const uint32_t stg = sSt + (c & 1) * 32768 + warp * 2048;
            uint32_t a[4][4];
#pragma unroll
            for (int j = 0; j < 4; j++) ldsm_x4(qb + j * 8192, a[j]);
            __syncwarp();
            if (lane == 0) {
                mbar_arrive(sBar + 64 + 8 * (c % NBUF));
                if (c >= 1 && warp == (c & 15) && c - 1 + NBUF < 16) {
                    const int cp = c - 1;
                    mbar_wait(sBar + 64 + 8 * (cp % NBUF), (cp / NBUF) & 1);
                    mbar_expect_tx(sBar + 8 * (cp % NBUF), 32768);
                    for (int j = 0; j < 4; j++) load_chunk(cp + NBUF, j);
                }
                if (c >= 2) asm volatile("cp.async.bulk.wait_group.read 1;" ::: "memory");
            }
            __syncwarp();
#pragma unroll
            for (int j = 0; j < 4; j++) {
#pragma unroll
                for (int i = 0; i < 4; i++) a[j][i] = phi_bf16x2(a[j][i]);
                float n0[4] = {0.f, 0.f, 0.f, 0.f}, n1[4] = {0.f, 0.f, 0.f, 0.f}, dn[4] = {0.f, 0.f, 0.f, 0.f};
                mma_bf16(n0, a[j], bf[j][0], bf[j][1]);
                mma_bf16(n1, a[j], bf[j][2], bf[j][3]);
                mma_bf16(dn, a[j], bf[j][4], bf[j][5]);
                const float i0 = rcp_fast(dn[0] + 1e-6f), i1 = rcp_fast(dn[2] + 1e-6f);
                stsm_x4(stg + lr * 128 + (((j * 2 + lc) ^ (lr & 7)) << 4),
                        pack_bf16(n0[0] * i0, n0[1] * i0), pack_bf16(n0[2] * i1, n0[3] * i1),
                        pack_bf16(n1[0] * i0, n1[1] * i0), pack_bf16(n1[2] * i1, n1[3] * i1));
            }
            fence_async_smem();
            __syncwarp();
            if (lane == 0) {
                tma_store_2d(tmO16, stg, cta * 128 + quad * 64, rc * 256 + warp * 16);
                bulk_commit();
            }
        }
    }
    if (lane == 0) { bulk_wait0(); fence_async_all(); }
    __syncthreads();
    if (tid == 0) signal_add(&g_cnt.oA);
    STAMP(1, 5);
}

__global__ void __launch_bounds__(512, 1) fused_kernel(const __grid_constant__ Maps mp) {
    extern __shared__ __align__(1024) uint8_t smem[];
    if (smem_u32(smem) != SM_BASE) __trap();
    STAMP(0, 0);
    if (blockIdx.x >= 128) {
        linattn_mid(smem, blockIdx.x - 128, &mp.o16);
    } else {
        phase_qkv(smem, mp);
        STAMP(1, 1);
        phase_attn(smem, mp);
        phase_out(smem, mp);
    }
}

typedef CUresult (*EncodeFn)(CUtensorMap*, CUtensorMapDataType, cuuint32_t, void*, const cuuint64_t*, const cuuint64_t*,
                             const cuuint32_t*, const cuuint32_t*, CUtensorMapInterleave, CUtensorMapSwizzle,
                             CUtensorMapL2promotion, CUtensorMapFloatOOBfill);

void make_map(EncodeFn enc, CUtensorMap* tm, const void* ptr, uint64_t cols, uint64_t rows, uint32_t boxc, uint32_t boxr) {
    cuuint64_t dims[2] = {cols, rows};
    cuuint64_t strides[1] = {cols * 2};
    cuuint32_t box[2] = {boxc, boxr};
    cuuint32_t es[2] = {1, 1};
    enc(tm, CU_TENSOR_MAP_DATA_TYPE_BFLOAT16, 2, const_cast<void*>(ptr), dims, strides, box, es, CU_TENSOR_MAP_INTERLEAVE_NONE,
        CU_TENSOR_MAP_SWIZZLE_128B, CU_TENSOR_MAP_L2_PROMOTION_L2_256B, CU_TENSOR_MAP_FLOAT_OOB_FILL_NONE);
}

struct HostState {
    bool init;
    const void* key[7];
    Maps mp;
};
HostState g_hs;

}

extern "C" void kernel_launch(void* const* d_in, const int* in_sizes, int n_in, void* d_out, int out_size) {
    (void)in_sizes; (void)n_in; (void)out_size;
    HostState& hs = g_hs;
    bool same = hs.init && hs.key[6] == d_out;
    for (int i = 0; i < 6 && same; i++) same = hs.key[i] == d_in[i];
    if (!same) {
        void* fn = nullptr;
        cudaDriverEntryPointQueryResult qr;
        cudaGetDriverEntryPoint("cuTensorMapEncodeTiled", &fn, cudaEnableDefault, &qr);
        EncodeFn enc = (EncodeFn)fn;
        void* po = nullptr;
        cudaGetSymbolAddress(&po, g_o);
        make_map(enc, &hs.mp.xA, d_in[0], 512, 2048, 64, 128);
        make_map(enc, &hs.mp.wA, d_in[1], 1536, 512, 64, 64);
        make_map(enc, &hs.mp.woA, d_in[2], 512, 512, 64, 64);
        make_map(enc, &hs.mp.xB, d_in[3], 512, 2048, 64, 128);
        make_map(enc, &hs.mp.wB, d_in[4], 1536, 512, 64, 64);
        make_map(enc, &hs.mp.woB, d_in[5], 512, 512, 64, 64);
        make_map(enc, &hs.mp.o, po, 1024, 2048, 64, 128);
        make_map(enc, &hs.mp.o16, po, 1024, 2048, 64, 16);
        make_map(enc, &hs.mp.out, d_out, 1024, 2048, 64, 64);
        cudaFuncSetAttribute(fused_kernel, cudaFuncAttributeMaxDynamicSharedMemorySize, SMEM_BYTES);
        for (int i = 0; i < 6; i++) hs.key[i] = d_in[i];
        hs.key[6] = d_out;
        hs.init = true;
    }
    fused_kernel<<<132, 512, SMEM_BYTES, cudaStreamPerThread>>>(hs.mp);
}
```

```cpp
#include <cuda_runtime.h>
#include <cuda_bf16.h>
#include <cuda.h>
#include <stdint.h>

namespace {

constexpr int S_LEN = 2048;
constexpr int NH = 32;

__device__ __align__(1024) uint16_t g_qB[NH * S_LEN * 16];
__device__ __align__(1024) uint16_t g_kB[NH * S_LEN * 16];
__device__ __align__(1024) uint16_t g_vB[NH * S_LEN * 16];
__device__ __align__(1024) uint16_t g_qA[NH * S_LEN * 16];
__device__ __align__(1024) uint16_t g_o[S_LEN * 1024];
__device__ __align__(16) float g_kvp[16 * NH * 272];
__device__ __align__(64) float g_qn[NH * 16];
__device__ __align__(64) float g_kn[NH * 16];

struct Counters {
    int qkvB[8];
    int qkvA[8];
    int oB[16 * 8];
    int oA;
    int done;
};
__device__ Counters g_cnt;

#define STAMP(k, s) do {} while (0)
#define DSTAMP(i) do {} while (0)

__device__ __forceinline__ uint32_t smem_u32(const void* p) { return (uint32_t)__cvta_generic_to_shared(p); }
__device__ __forceinline__ void wg_fence() { asm volatile("wgmma.fence.sync.aligned;" ::: "memory"); }
__device__ __forceinline__ void wg_commit() { asm volatile("wgmma.commit_group.sync.aligned;" ::: "memory"); }
template <int N> __device__ __forceinline__ void wg_wait() { asm volatile("wgmma.wait_group.sync.aligned %0;" ::"n"(N) : "memory"); }
__device__ __forceinline__ void mbar_init(uint32_t bar, uint32_t cnt) { asm volatile("mbarrier.init.shared::cta.b64 [%0], %1;" ::"r"(bar), "r"(cnt)); }
__device__ __forceinline__ void mbar_expect_tx(uint32_t bar, uint32_t bytes) {
    asm volatile("mbarrier.arrive.expect_tx.shared::cta.b64 _, [%0], %1;" ::"r"(bar), "r"(bytes) : "memory");
}
__device__ __forceinline__ void mbar_wait(uint32_t bar, uint32_t parity) {
    asm volatile(
        "{.reg .pred p;\n"
        "WAIT_LOOP:\n"
        "mbarrier.try_wait.parity.shared::cta.b64 p, [%0], %1;\n"
        "@p bra WAIT_DONE;\n"
        "bra WAIT_LOOP;\n"
        "WAIT_DONE:\n}" ::"r"(bar), "r"(parity) : "memory");
}
__device__ __forceinline__ void mbar_arrive(uint32_t bar) { asm volatile("mbarrier.arrive.shared::cta.b64 _, [%0];" ::"r"(bar) : "memory"); }
__device__ __forceinline__ void fence_mbar_init() { asm volatile("fence.mbarrier_init.release.cluster;" ::: "memory"); }
__device__ __forceinline__ void fence_async_smem() { asm volatile("fence.proxy.async.shared::cta;" ::: "memory"); }
#define SPIN_NS 100
__device__ __forceinline__ void spin_ge(const int* p, int target) {
    int it = 0;
    while (true) {
        int v;
        asm volatile("ld.acquire.gpu.global.s32 %0, [%1];" : "=r"(v) : "l"(p) : "memory");
        if (v >= target) break;
        if (++it > (1 << 22)) __trap();
        __nanosleep(SPIN_NS);
    }
}
__device__ __forceinline__ void finish_ticket() {
    if (atomicAdd(&g_cnt.done, 1) == (int)gridDim.x - 1) {
        int* c = (int*)&g_cnt;
        for (int i = 0; i < (int)(sizeof(Counters) / sizeof(int)); i++) c[i] = 0;
    }
}
__device__ __forceinline__ void signal_add(int* p) { asm volatile("red.release.gpu.global.add.s32 [%0], 1;" ::"l"(p) : "memory"); }
__device__ __forceinline__ void fence_async_all() { asm volatile("fence.proxy.async.global;" ::: "memory"); }
__device__ __forceinline__ void named_bar(int id, int n) { asm volatile("bar.sync %0, %1;" ::"r"(id), "r"(n) : "memory"); }

__device__ __forceinline__ void bulk_g2s(uint32_t dst, const void* src, uint32_t bytes, uint32_t bar) {
    asm volatile("cp.async.bulk.shared::cluster.global.mbarrier::complete_tx::bytes [%0], [%1], %2, [%3];" ::"r"(dst), "l"(src), "r"(bytes), "r"(bar) : "memory");
}
__device__ __forceinline__ void bulk_commit() { asm volatile("cp.async.bulk.commit_group;" ::: "memory"); }
__device__ __forceinline__ void bulk_wait0() { asm volatile("cp.async.bulk.wait_group 0;" ::: "memory"); }
__device__ __forceinline__ void tma_load_2d(uint32_t dst, const CUtensorMap* tm, int c0, int c1, uint32_t bar) {
    asm volatile("cp.async.bulk.tensor.2d.shared::cluster.global.mbarrier::complete_tx::bytes [%0], [%1, {%3, %4}], [%2];" ::"r"(dst), "l"(tm), "r"(bar), "r"(c0), "r"(c1) : "memory");
}
__device__ __forceinline__ void tma_store_2d(const CUtensorMap* tm, uint32_t src, int c0, int c1) {
    asm volatile("cp.async.bulk.tensor.2d.global.shared::cta.bulk_group [%0, {%2, %3}], [%1];" ::"l"(tm), "r"(src), "r"(c0), "r"(c1) : "memory");
}
__device__ __forceinline__ void tma_prefetch_desc(const CUtensorMap* tm) { asm volatile("prefetch.tensormap [%0];" ::"l"(tm) : "memory"); }

__device__ __forceinline__ uint32_t pack_bf16(float lo, float hi) {
    uint32_t r; asm("cvt.rn.bf16x2.f32 %0, %1, %2;" : "=r"(r) : "f"(hi), "f"(lo)); return r;
}
__device__ __forceinline__ float ex2f(float x) { float r; asm("ex2.approx.ftz.f32 %0, %1;" : "=f"(r) : "f"(x)); return r; }
__device__ __forceinline__ float bf_lo(uint32_t p) { return __uint_as_float(p << 16); }
__device__ __forceinline__ float bf_hi(uint32_t p) { return __uint_as_float(p & 0xFFFF0000u); }
__device__ __forceinline__ void stsm_x4(uint32_t addr, uint32_t r0, uint32_t r1, uint32_t r2, uint32_t r3) {
    asm volatile("stmatrix.sync.aligned.m8n8.x4.shared.b16 [%0], {%1,%2,%3,%4};" ::"r"(addr), "r"(r0), "r"(r1), "r"(r2), "r"(r3) : "memory");
}
__device__ __forceinline__ void ldsm_x4(uint32_t addr, uint32_t* r) {
    asm volatile("ldmatrix.sync.aligned.m8n8.x4.shared.b16 {%0,%1,%2,%3}, [%4];" : "=r"(r[0]), "=r"(r[1]), "=r"(r[2]), "=r"(r[3]) : "r"(addr) : "memory");
}
__device__ __forceinline__ void ldsm_x4_t(uint32_t addr, uint32_t* r) {
    asm volatile("ldmatrix.sync.aligned.m8n8.x4.trans.shared.b16 {%0,%1,%2,%3}, [%4];" : "=r"(r[0]), "=r"(r[1]), "=r"(r[2]), "=r"(r[3]) : "r"(addr) : "memory");
}
__device__ __forceinline__ void mma_bf16(float* d, const uint32_t* a, uint32_t b0, uint32_t b1) {
    asm volatile("mma.sync.aligned.m16n8k16.row.col.f32.bf16.bf16.f32 {%0,%1,%2,%3}, {%4,%5,%6,%7}, {%8,%9}, {%0,%1,%2,%3};"
                 : "+f"(d[0]), "+f"(d[1]), "+f"(d[2]), "+f"(d[3]) : "r"(a[0]), "r"(a[1]), "r"(a[2]), "r"(a[3]), "r"(b0), "r"(b1));
}
__device__ __forceinline__ uint32_t phi_bf16x2(uint32_t p) {
    const float t0 = bf_lo(p), t1 = bf_hi(p);
    const float a0 = fmaf(t0 + fabsf(t0), 0.5f, ex2f((t0 - fabsf(t0)) * 0.7213475204444817f));
    const float a1 = fmaf(t1 + fabsf(t1), 0.5f, ex2f((t1 - fabsf(t1)) * 0.7213475204444817f));
    const uint32_t a = pack_bf16(a0, a1);
    uint32_t r;
    asm("add.rn.bf16x2 %0, %1, %2;" : "=r"(r) : "r"(a), "r"(0x35863586u));
    return r;
}
__device__ __forceinline__ float rcp_fast(float x) { float r; asm("rcp.approx.ftz.f32 %0, %1;" : "=f"(r) : "f"(x)); return r; }
template <typename T, int N> __device__ __forceinline__ void fence_regs(T (&r)[N]) {
#pragma unroll
    for (int i = 0; i < N; i++) {
        if constexpr (sizeof(T) == 4 && T(0.5) != T(0)) asm volatile("" : "+f"(r[i])::"memory");
        else asm volatile("" : "+r"(r[i])::"memory");
    }
}

__device__ __forceinline__ void wgmma_ss_n192_tb(float* d, uint64_t da, uint64_t db, int sd) {
  asm volatile("{.reg .pred p; setp.ne.b32 p, %98, 0; wgmma.mma_async.sync.aligned.m64n192k16.f32.bf16.bf16 {%0,%1,%2,%3,%4,%5,%6,%7,%8,%9,%10,%11,%12,%13,%14,%15,%16,%17,%18,%19,%20,%21,%22,%23,%24,%25,%26,%27,%28,%29,%30,%31,%32,%33,%34,%35,%36,%37,%38,%39,%40,%41,%42,%43,%44,%45,%46,%47,%48,%49,%50,%51,%52,%53,%54,%55,%56,%57,%58,%59,%60,%61,%62,%63,%64,%65,%66,%67,%68,%69,%70,%71,%72,%73,%74,%75,%76,%77,%78,%79,%80,%81,%82,%83,%84,%85,%86,%87,%88,%89,%90,%91,%92,%93,%94,%95}, %96, %97, p, 1, 1, 0, 1;}"
    : "+f"(d[0]), "+f"(d[1]), "+f"(d[2]), "+f"(d[3]), "+f"(d[4]), "+f"(d[5]), "+f"(d[6]), "+f"(d[7]), "+f"(d[8]), "+f"(d[9]), "+f"(d[10]), "+f"(d[11]), "+f"(d[12]), "+f"(d[13]), "+f"(d[14]), "+f"(d[15]), "+f"(d[16]), "+f"(d[17]), "+f"(d[18]), "+f"(d[19]), "+f"(d[20]), "+f"(d[21]), "+f"(d[22]), "+f"(d[23]), "+f"(d[24]), "+f"(d[25]), "+f"(d[26]), "+f"(d[27]), "+f"(d[28]), "+f"(d[29]), "+f"(d[30]), "+f"(d[31]), "+f"(d[32]), "+f"(d[33]), "+f"(d[34]), "+f"(d[35]), "+f"(d[36]), "+f"(d[37]), "+f"(d[38]), "+f"(d[39]), "+f"(d[40]), "+f"(d[41]), "+f"(d[42]), "+f"(d[43]), "+f"(d[44]), "+f"(d[45]), "+f"(d[46]), "+f"(d[47]), "+f"(d[48]), "+f"(d[49]), "+f"(d[50]), "+f"(d[51]), "+f"(d[52]), "+f"(d[53]), "+f"(d[54]), "+f"(d[55]), "+f"(d[56]), "+f"(d[57]), "+f"(d[58]), "+f"(d[59]), "+f"(d[60]), "+f"(d[61]), "+f"(d[62]), "+f"(d[63]), "+f"(d[64]), "+f"(d[65]), "+f"(d[66]), "+f"(d[67]), "+f"(d[68]), "+f"(d[69]), "+f"(d[70]), "+f"(d[71]), "+f"(d[72]), "+f"(d[73]), "+f"(d[74]), "+f"(d[75]), "+f"(d[76]), "+f"(d[77]), "+f"(d[78]), "+f"(d[79]), "+f"(d[80]), "+f"(d[81]), "+f"(d[82]), "+f"(d[83]), "+f"(d[84]), "+f"(d[85]), "+f"(d[86]), "+f"(d[87]), "+f"(d[88]), "+f"(d[89]), "+f"(d[90]), "+f"(d[91]), "+f"(d[92]), "+f"(d[93]), "+f"(d[94]), "+f"(d[95]) : "l"(da), "l"(db), "r"(sd));
}
__device__ __forceinline__ void wgmma_ss_n128_tb(float* d, uint64_t da, uint64_t db, int sd) {
  asm volatile("{.reg .pred p; setp.ne.b32 p, %66, 0; wgmma.mma_async.sync.aligned.m64n128k16.f32.bf16.bf16 {%0,%1,%2,%3,%4,%5,%6,%7,%8,%9,%10,%11,%12,%13,%14,%15,%16,%17,%18,%19,%20,%21,%22,%23,%24,%25,%26,%27,%28,%29,%30,%31,%32,%33,%34,%35,%36,%37,%38,%39,%40,%41,%42,%43,%44,%45,%46,%47,%48,%49,%50,%51,%52,%53,%54,%55,%56,%57,%58,%59,%60,%61,%62,%63}, %64, %65, p, 1, 1, 0, 1;}"
    : "+f"(d[0]), "+f"(d[1]), "+f"(d[2]), "+f"(d[3]), "+f"(d[4]), "+f"(d[5]), "+f"(d[6]), "+f"(d[7]), "+f"(d[8]), "+f"(d[9]), "+f"(d[10]), "+f"(d[11]), "+f"(d[12]), "+f"(d[13]), "+f"(d[14]), "+f"(d[15]), "+f"(d[16]), "+f"(d[17]), "+f"(d[18]), "+f"(d[19]), "+f"(d[20]), "+f"(d[21]), "+f"(d[22]), "+f"(d[23]), "+f"(d[24]), "+f"(d[25]), "+f"(d[26]), "+f"(d[27]), "+f"(d[28]), "+f"(d[29]), "+f"(d[30]), "+f"(d[31]), "+f"(d[32]), "+f"(d[33]), "+f"(d[34]), "+f"(d[35]), "+f"(d[36]), "+f"(d[37]), "+f"(d[38]), "+f"(d[39]), "+f"(d[40]), "+f"(d[41]), "+f"(d[42]), "+f"(d[43]), "+f"(d[44]), "+f"(d[45]), "+f"(d[46]), "+f"(d[47]), "+f"(d[48]), "+f"(d[49]), "+f"(d[50]), "+f"(d[51]), "+f"(d[52]), "+f"(d[53]), "+f"(d[54]), "+f"(d[55]), "+f"(d[56]), "+f"(d[57]), "+f"(d[58]), "+f"(d[59]), "+f"(d[60]), "+f"(d[61]), "+f"(d[62]), "+f"(d[63]) : "l"(da), "l"(db), "r"(sd));
}
template<int SD> __device__ __forceinline__ void wgmma_rs_n64(float* d, const uint32_t* a, uint64_t db) {
  asm volatile("{.reg .pred p; setp.ne.b32 p, %37, 0; wgmma.mma_async.sync.aligned.m64n64k16.f32.bf16.bf16 {%0,%1,%2,%3,%4,%5,%6,%7,%8,%9,%10,%11,%12,%13,%14,%15,%16,%17,%18,%19,%20,%21,%22,%23,%24,%25,%26,%27,%28,%29,%30,%31}, {%32,%33,%34,%35}, %36, p, 1, 1, 0;}"
    : "+f"(d[0]), "+f"(d[1]), "+f"(d[2]), "+f"(d[3]), "+f"(d[4]), "+f"(d[5]), "+f"(d[6]), "+f"(d[7]), "+f"(d[8]), "+f"(d[9]), "+f"(d[10]), "+f"(d[11]), "+f"(d[12]), "+f"(d[13]), "+f"(d[14]), "+f"(d[15]), "+f"(d[16]), "+f"(d[17]), "+f"(d[18]), "+f"(d[19]), "+f"(d[20]), "+f"(d[21]), "+f"(d[22]), "+f"(d[23]), "+f"(d[24]), "+f"(d[25]), "+f"(d[26]), "+f"(d[27]), "+f"(d[28]), "+f"(d[29]), "+f"(d[30]), "+f"(d[31]) : "r"(a[0]), "r"(a[1]), "r"(a[2]), "r"(a[3]), "l"(db), "n"(SD));
}
template<int SD> __device__ __forceinline__ void wgmma_rs_n24(float* d, const uint32_t* a, uint64_t db) {
  asm volatile("{.reg .pred p; setp.ne.b32 p, %17, 0; wgmma.mma_async.sync.aligned.m64n24k16.f32.bf16.bf16 {%0,%1,%2,%3,%4,%5,%6,%7,%8,%9,%10,%11}, {%12,%13,%14,%15}, %16, p, 1, 1, 0;}"
    : "+f"(d[0]), "+f"(d[1]), "+f"(d[2]), "+f"(d[3]), "+f"(d[4]), "+f"(d[5]), "+f"(d[6]), "+f"(d[7]), "+f"(d[8]), "+f"(d[9]), "+f"(d[10]), "+f"(d[11]) : "r"(a[0]), "r"(a[1]), "r"(a[2]), "r"(a[3]), "l"(db), "n"(SD));
}
template<int SD> __device__ __forceinline__ void wgmma_rs_n32(float* d, const uint32_t* a, uint64_t db) {
  asm volatile("{.reg .pred p; setp.ne.b32 p, %21, 0; wgmma.mma_async.sync.aligned.m64n32k16.f32.bf16.bf16 {%0,%1,%2,%3,%4,%5,%6,%7,%8,%9,%10,%11,%12,%13,%14,%15}, {%16,%17,%18,%19}, %20, p, 1, 1, 0;}"
    : "+f"(d[0]), "+f"(d[1]), "+f"(d[2]), "+f"(d[3]), "+f"(d[4]), "+f"(d[5]), "+f"(d[6]), "+f"(d[7]), "+f"(d[8]), "+f"(d[9]), "+f"(d[10]), "+f"(d[11]), "+f"(d[12]), "+f"(d[13]), "+f"(d[14]), "+f"(d[15]) : "r"(a[0]), "r"(a[1]), "r"(a[2]), "r"(a[3]), "l"(db), "n"(SD));
}
template<int SD> __device__ __forceinline__ void wgmma_rs_n40(float* d, const uint32_t* a, uint64_t db) {
  asm volatile("{.reg .pred p; setp.ne.b32 p, %25, 0; wgmma.mma_async.sync.aligned.m64n40k16.f32.bf16.bf16 {%0,%1,%2,%3,%4,%5,%6,%7,%8,%9,%10,%11,%12,%13,%14,%15,%16,%17,%18,%19}, {%20,%21,%22,%23}, %24, p, 1, 1, 0;}"
    : "+f"(d[0]), "+f"(d[1]), "+f"(d[2]), "+f"(d[3]), "+f"(d[4]), "+f"(d[5]), "+f"(d[6]), "+f"(d[7]), "+f"(d[8]), "+f"(d[9]), "+f"(d[10]), "+f"(d[11]), "+f"(d[12]), "+f"(d[13]), "+f"(d[14]), "+f"(d[15]), "+f"(d[16]), "+f"(d[17]), "+f"(d[18]), "+f"(d[19]) : "r"(a[0]), "r"(a[1]), "r"(a[2]), "r"(a[3]), "l"(db), "n"(SD));
}
template<int SD> __device__ __forceinline__ void wgmma_rs_n24_tb(float* d, const uint32_t* a, uint64_t db) {
  asm volatile("{.reg .pred p; setp.ne.b32 p, %17, 0; wgmma.mma_async.sync.aligned.m64n24k16.f32.bf16.bf16 {%0,%1,%2,%3,%4,%5,%6,%7,%8,%9,%10,%11}, {%12,%13,%14,%15}, %16, p, 1, 1, 1;}"
    : "+f"(d[0]), "+f"(d[1]), "+f"(d[2]), "+f"(d[3]), "+f"(d[4]), "+f"(d[5]), "+f"(d[6]), "+f"(d[7]), "+f"(d[8]), "+f"(d[9]), "+f"(d[10]), "+f"(d[11]) : "r"(a[0]), "r"(a[1]), "r"(a[2]), "r"(a[3]), "l"(db), "n"(SD));
}

constexpr uint64_t DESC_SW128 = (uint64_t)1 << 62;
constexpr uint64_t DESC_SW32 = (uint64_t)3 << 62;
__device__ __forceinline__ uint64_t mk_desc(uint64_t sw, uint32_t addr, uint32_t lbo, uint32_t sbo) {
    return sw | ((uint64_t)(sbo >> 4) << 32) | ((uint64_t)(lbo >> 4) << 16) | (uint64_t)((addr & 0x3FFFF) >> 4);
}

constexpr uint32_t SM_BASE = 1024;
constexpr uint32_t P1_STAGE = 40960;
constexpr uint32_t P1_STGA = 98304;
constexpr uint32_t P1_RED = 147456;
constexpr uint32_t AT_Q = 0, AT_K = 16384, AT_V = 81920, AT_TAB = 163840, AT_ONES = 230400, AT_CT = 230912;
constexpr uint32_t P3_O = AT_TAB;
constexpr uint32_t BAR = 229376;
constexpr uint32_t B_FULL = BAR, B_EMPTY = BAR + 32;
constexpr uint32_t B_KV = BAR + 96, B_Q = BAR + 160, B_CONS = BAR + 168, B_WFULL = BAR + 232, B_OFULL = BAR + 296, B_OEMPTY = BAR + 328;
constexpr uint32_t B_STFREE = BAR + 360;
constexpr uint32_t OFF_MAX = BAR + 416, OFF_NORM = BAR + 512;
constexpr int SMEM_BYTES = BAR + 1024 + 832;
constexpr uint32_t B_TAB = BAR + 64;
constexpr float QSCALE = 0.25f * 1.4426950408889634f;

struct Maps { CUtensorMap xA, xB, wA, wB, o, o16, woA, woB, out; };

__device__ __forceinline__ void phase_qkv(uint8_t* smem, const Maps& mp) {
    constexpr uint32_t sb = SM_BASE;
    const int tid = threadIdx.x, warp = tid >> 5, lane = tid & 31;
    const int nt = blockIdx.x & 7, mt = blockIdx.x >> 3;
    float* sMax = (float*)(smem + OFF_MAX);
    auto produce = [&](int kb) {
        const int s = kb & 3;
        const uint32_t full = sb + B_FULL + 8 * s, st = sb + s * P1_STAGE;
        mbar_expect_tx(full, P1_STAGE);
        tma_load_2d(st, kb < 8 ? &mp.xB : &mp.xA, (kb & 7) * 64, mt * 128, full);
#pragma unroll
        for (int j = 0; j < 3; j++) tma_load_2d(st + 16384 + j * 8192, kb < 8 ? &mp.wB : &mp.wA, j * 512 + nt * 64, (kb & 7) * 64, full);
    };
    if (tid == 0) {
        tma_prefetch_desc(&mp.xB); tma_prefetch_desc(&mp.wB);
        for (int i = 0; i < 4; i++) { mbar_init(sb + B_FULL + 8 * i, 1); mbar_init(sb + B_EMPTY + 8 * i, 2); }
        fence_mbar_init();
        DSTAMP(28);
        for (int kb = 0; kb < 4; kb++) produce(kb);
        DSTAMP(29);
        tma_prefetch_desc(&mp.xA); tma_prefetch_desc(&mp.wA);
    }
    if (tid == 32) {
                for (int i = 0; i < 4; i++) mbar_init(sb + B_STFREE + 8 * i, 2);
        mbar_init(sb + B_Q, 1); mbar_init(sb + B_TAB, 256);
        for (int i = 0; i < 8; i++) { mbar_init(sb + B_KV + 8 * i, 1); mbar_init(sb + B_CONS + 8 * i, 4); mbar_init(sb + B_WFULL + 8 * i, 1); }
        for (int i = 0; i < 4; i++) { mbar_init(sb + B_OFULL + 8 * i, 1); mbar_init(sb + B_OEMPTY + 8 * i, 2); }
        fence_mbar_init();
    }
    if (tid >= 64 && tid < 72) sMax[tid - 64] = 0.f;
    __syncthreads();
    STAMP(0, 1);

    const int wg = __shfl_sync(0xffffffffu, warp >> 2, 0);
    const int branchB = wg < 2;
    const int wh = wg & 1;
    const int kb0 = branchB ? 0 : 8;
    float acc[96];
#pragma unroll
    for (int i = 0; i < 96; i++) acc[i] = 0.f;
    fence_regs(acc);
    if (!branchB) {
        const int w = warp & 7, j = w * 32 + lane;
        const float f = (j + 0.5f) * (1.f / 256.f);
        const uint32_t val = (uint32_t)(__float2int_rn((exp2f(f) - 1.f) * 128.f) - (j >> 1) + (63 << 7) - 0x8000);
        uint4* tb = (uint4*)(smem + AT_TAB) + w * 32 * 8 + lane;
#pragma unroll
        for (int i = 0; i < 8; i++) {
            const uint32_t v = __shfl_sync(0xffffffffu, val, i * 4 + (lane >> 3));
            tb[i * 32] = make_uint4(v, v, v, v);
            tb[2048 + i * 32] = make_uint4(v << 16, v << 16, v << 16, v << 16);
        }
        if (w == 0) { for (int i = lane; i < 128; i += 32) ((uint32_t*)(smem + AT_ONES))[i] = 0x3F803F80u; }
        if (w == 1) {
            for (int i = lane; i < 64; i += 32) {
                const int r = i >> 3, ww = i & 7, chunk = (ww >> 2) ^ (r >> 2);
                ((uint32_t*)(smem + AT_CT))[i] = (chunk == 0 && (ww & 3) == 0) ? 0x000043A0u : 0u;
            }
        }
        if (w == 2 && lane < 8) ((uint32_t*)(smem + AT_CT + 256))[lane] = lane < 2 ? 0x00003F80u : 0u;
        fence_async_smem();
        mbar_arrive(sb + B_TAB);
        named_bar(3, 512);
    }
    const uint64_t dA0 = mk_desc(DESC_SW128, sb + wh * 8192, 16, 1024);
#pragma unroll
    for (int i = 0; i < 8; i++) {
        const int kb = kb0 + i, s = i & 3;
        mbar_wait(sb + B_FULL + 8 * s, (i >> 2) & 1);
        if (kb == 0) STAMP(0, 2);
        if ((tid & 255) == 0) DSTAMP(kb);
        const uint64_t dA = dA0 + (uint64_t)(s * (P1_STAGE >> 4)), dB = mk_desc(DESC_SW128, sb + s * P1_STAGE + 16384, 8192, 1024);
        wg_fence();
#pragma unroll
        for (int k = 0; k < 4; k++) wgmma_ss_n192_tb(acc, dA + k * 2, dB + k * 128, 1);
        wg_commit();
        if (i == 7 && branchB) asm volatile("bar.arrive 3, 512;" ::: "memory");
        if (i > 0) {
            wg_wait<1>();
            if (i >= 5 && !branchB && (tid & 127) == 0) mbar_arrive(sb + B_STFREE + 8 * (i - 5));
            if (kb + 3 < 16) {
                const uint32_t eb = sb + B_EMPTY + 8 * ((i - 1) & 3);
                if ((tid & 127) == 0) {
                    mbar_arrive(eb);
                    if (wh == 0) { mbar_wait(eb, ((i - 1) >> 2) & 1); produce(kb + 3); }
                }
                __syncwarp();
            }
        }
    }
    wg_wait<0>();
    fence_regs(acc);
    STAMP(0, 3);

    const int wq = warp & 3, g = lane >> 2, t = lane & 3;
    const int lr = (lane & 7) + ((lane >> 3) & 1) * 8;
    const int lc = lane >> 4;
    const int row0 = mt * 128;
    const int w8 = warp & 7;
    if (branchB) {
        {
            const uint32_t eb = sb + B_EMPTY + 8 * 3;
            if ((tid & 127) == 0) {
                mbar_arrive(eb);
                if (wh == 0) { mbar_wait(eb, 1); produce(11); }
            }
            __syncwarp();
        }
        const int orow = g + (t >> 1) * 8;
        const uint32_t ooff = (uint32_t)(row0 + wh * 64 + wq * 16 + orow) * 32 + (((t & 1) ^ ((orow & 7) >> 2)) << 4);
        const bool o1 = t & 1, o2 = t & 2;
        uint32_t mymax = 0;
#pragma unroll
        for (int sl = 0; sl < 12; sl++) {
            float* a = acc + sl * 8;
            if (sl < 4) {
#pragma unroll
                for (int i = 0; i < 8; i++) a[i] *= QSCALE;
            }
            if (sl < 8) {
                const float n0 = fmaf(a[0], a[0], fmaf(a[1], a[1], fmaf(a[4], a[4], a[5] * a[5])));
                const float n1 = fmaf(a[2], a[2], fmaf(a[3], a[3], fmaf(a[6], a[6], a[7] * a[7])));
                const uint32_t m = __reduce_max_sync(0xffffffffu, __float_as_uint(fmaxf(n0, n1)));
                if (lane == sl) mymax = m;
            }
            const uint32_t w0 = pack_bf16(a[0], a[1]), w2 = pack_bf16(a[2], a[3]), w1 = pack_bf16(a[4], a[5]), w3 = pack_bf16(a[6], a[7]);
            const uint32_t r0 = __shfl_xor_sync(0xffffffffu, o1 ? w0 : w1, 1), r1 = __shfl_xor_sync(0xffffffffu, o1 ? w2 : w3, 1);
            const uint32_t x0 = o1 ? r0 : w0, x1 = o1 ? w1 : r0, y0 = o1 ? r1 : w2, y1 = o1 ? w3 : r1;
            const uint32_t q0 = __shfl_xor_sync(0xffffffffu, o2 ? x0 : y0, 2), q1 = __shfl_xor_sync(0xffffffffu, o2 ? x1 : y1, 2);
            uint4 val;
            val.x = o2 ? q0 : x0; val.y = o2 ? q1 : x1; val.z = o2 ? y0 : q0; val.w = o2 ? y1 : q1;
            const int ty = sl >> 2, head = nt * 4 + (sl & 3);
            uint8_t* dst = (uint8_t*)((ty == 0 ? g_qB : (ty == 1 ? g_kB : g_vB)) + (size_t)head * S_LEN * 16);
            *(uint4*)(dst + ooff) = val;
        }
        if (lane < 8) atomicMax((unsigned int*)&sMax[lane], mymax);
        named_bar(1, 256);
        if (tid == 0) DSTAMP(16);
        if (w8 == 7 && lane >= 8 && lane < 16) { const int i = lane - 8; (i < 4 ? g_qn : g_kn)[(nt * 4 + (i & 3)) * 16 + mt] = sMax[i]; }
        named_bar(1, 256);
        const int h = blockIdx.x >> 2, qb = blockIdx.x & 3;
        if (tid == 0) signal_add(&g_cnt.qkvB[nt]);
        auto ld_k = [&](int c) {
            mbar_expect_tx(sb + B_KV + 8 * c, 16384);
            bulk_g2s(sb + AT_K + c * 8192, g_kB + ((size_t)h * S_LEN + c * 256) * 16, 8192, sb + B_KV + 8 * c);
        };
        auto ld_v = [&](int c) { bulk_g2s(sb + AT_V + c * 8192, g_vB + ((size_t)h * S_LEN + c * 256) * 16, 8192, sb + B_KV + 8 * c); };
        if (tid == 32) {
            spin_ge(&g_cnt.qkvB[h >> 2], 16);
            fence_async_all();
            mbar_wait(sb + B_STFREE, 0);
            mbar_expect_tx(sb + B_Q, 16384 + 128);
            bulk_g2s(sb + AT_Q, g_qB + ((size_t)h * S_LEN + qb * 512) * 16, 16384, sb + B_Q);
            ld_k(0);
            bulk_g2s(sb + OFF_NORM, g_qn + h * 16, 64, sb + B_Q);
            bulk_g2s(sb + OFF_NORM + 64, g_kn + h * 16, 64, sb + B_Q);
            DSTAMP(27);
            mbar_wait(sb + B_STFREE + 16, 0);
            ld_v(0); ld_k(1); ld_v(1);
        }
        __syncwarp();
        STAMP(0, 5);
    } else {
        if ((tid & 127) == 0) mbar_arrive(sb + B_STFREE + 8 * 3);
        if (tid == 256) DSTAMP(22);
        named_bar(2, 256);
        const uint32_t stg = sb + P1_STGA;
        const uint32_t stAddr = stg + (wh * 64 + wq * 16 + lr) * 32 + (((lc ^ ((lr & 7) >> 2))) << 4);
#pragma unroll
        for (int sl = 0; sl < 12; sl++) {
            float* a = acc + sl * 8;
            uint32_t p0 = pack_bf16(a[0], a[1]), p1 = pack_bf16(a[2], a[3]), p2 = pack_bf16(a[4], a[5]), p3 = pack_bf16(a[6], a[7]);
            if (sl >= 4 && sl < 8) { p0 = phi_bf16x2(p0); p1 = phi_bf16x2(p1); p2 = phi_bf16x2(p2); p3 = phi_bf16x2(p3); }
            stsm_x4(stAddr + sl * 4096, p0, p1, p2, p3);
        }
        named_bar(2, 256);
        if (tid == 256) DSTAMP(23);
#pragma unroll
        for (int sl = 0; sl < 4; sl++)
            *(uint4*)((uint8_t*)(g_qA + ((size_t)(nt * 4 + sl) * S_LEN + row0) * 16) + (tid - 256) * 16) = *(const uint4*)(smem + P1_STGA + sl * 4096 + (tid - 256) * 16);
        const int hh = w8 & 3;
        const uint32_t pkb = stg + (4 + hh) * 4096 + wh * 2048, vb = stg + (8 + hh) * 4096 + wh * 2048;
        float kv0[4] = {0.f, 0.f, 0.f, 0.f}, kv1[4] = {0.f, 0.f, 0.f, 0.f}, zz[4] = {0.f, 0.f, 0.f, 0.f};
        const int ar = (lane & 7) + (lane >> 4) * 8, ac = (lane >> 3) & 1;
        const int br = (lane & 7) + ((lane >> 3) & 1) * 8, bc = lane >> 4;
#pragma unroll
        for (int ks = 0; ks < 4; ks++) {
            uint32_t af[4], bf[4];
            ldsm_x4_t(pkb + (ks * 16 + ar) * 32 + ((ac ^ ((ar & 7) >> 2)) << 4), af);
            ldsm_x4_t(vb + (ks * 16 + br) * 32 + ((bc ^ ((br & 7) >> 2)) << 4), bf);
            mma_bf16(kv0, af, bf[0], bf[1]);
            mma_bf16(kv1, af, bf[2], bf[3]);
            mma_bf16(zz, af, 0x3F803F80u, 0x3F803F80u);
        }
        if (tid == 256) DSTAMP(24);
        float* rp = (float*)(smem + P1_RED) + hh * 272;
        if (wh == 1) {
            rp[g * 16 + 2 * t] = kv0[0]; rp[g * 16 + 2 * t + 1] = kv0[1];
            rp[(g + 8) * 16 + 2 * t] = kv0[2]; rp[(g + 8) * 16 + 2 * t + 1] = kv0[3];
            rp[g * 16 + 8 + 2 * t] = kv1[0]; rp[g * 16 + 8 + 2 * t + 1] = kv1[1];
            rp[(g + 8) * 16 + 8 + 2 * t] = kv1[2]; rp[(g + 8) * 16 + 8 + 2 * t + 1] = kv1[3];
            if (t == 0) { rp[256 + g] = zz[0]; rp[256 + g + 8] = zz[2]; }
        }
        named_bar(2, 256);
        if (wh == 0) {
            float* gp = g_kvp + (size_t)(mt * NH + nt * 4 + hh) * 272;
            *(float2*)(gp + g * 16 + 2 * t) = make_float2(kv0[0] + rp[g * 16 + 2 * t], kv0[1] + rp[g * 16 + 2 * t + 1]);
            *(float2*)(gp + (g + 8) * 16 + 2 * t) = make_float2(kv0[2] + rp[(g + 8) * 16 + 2 * t], kv0[3] + rp[(g + 8) * 16 + 2 * t + 1]);
            *(float2*)(gp + g * 16 + 8 + 2 * t) = make_float2(kv1[0] + rp[g * 16 + 8 + 2 * t], kv1[1] + rp[g * 16 + 8 + 2 * t + 1]);
            *(float2*)(gp + (g + 8) * 16 + 8 + 2 * t) = make_float2(kv1[2] + rp[(g + 8) * 16 + 8 + 2 * t], kv1[3] + rp[(g + 8) * 16 + 8 + 2 * t + 1]);
            if (t == 0) { gp[256 + g] = zz[0] + rp[256 + g]; gp[256 + g + 8] = zz[2] + rp[256 + g + 8]; }
        }
        STAMP(0, 6);
    }
}

constexpr int AT_NT = 64;
#define AT_NP_V 32
#define AT_NP2_V 40
constexpr int AT_NP = AT_NP_V, AT_NP2 = AT_NP2_V;
constexpr float AT_SAFE2 = 56.f * 56.f;

__device__ __forceinline__ uint32_t ex2_tab2(float ya, float yb, uint32_t lane4) {
    const uint32_t a = __float_as_uint(ya), b = __float_as_uint(yb);
    uint32_t aa, ab, ta, tb, L;
    asm("lop3.b32 %0, %1, 0x7F80, %2, 0xEA;" : "=r"(aa) : "r"(a), "r"(lane4));
    asm("lop3.b32 %0, %1, 0x7F80, %2, 0xEA;" : "=r"(ab) : "r"(b), "r"(lane4));
    asm volatile("ld.shared.u32 %0, [%1+%2];" : "=r"(ta) : "r"(aa), "n"(SM_BASE + AT_TAB));
    asm volatile("ld.shared.u32 %0, [%1+%2];" : "=r"(tb) : "r"(ab), "n"(SM_BASE + AT_TAB + 32768));
    asm("prmt.b32 %0, %1, %2, 0x6521;" : "=r"(L) : "r"(a), "r"(b));
    return L + ta + tb;
}
template <int NT, int NP>
__device__ __forceinline__ void att_exp(const float* s, uint32_t* p, uint32_t lane4) {
    constexpr int PP = NP / 4, TOT = NT / 4;
#pragma unroll
    for (int i = 0; i < TOT; i++) {
        const int nb = (i * PP) / TOT, na = ((i + 1) * PP) / TOT;
        if (na != nb) p[nb] = ex2_tab2(s[2 * nb], s[2 * nb + 1], lane4);
        else { const int im = PP + i - nb; p[im] = pack_bf16(ex2f(s[2 * im]), ex2f(s[2 * im + 1])); }
    }
}

__device__ __forceinline__ void mbar_arrive_elect(uint32_t bar) {
    asm volatile("{.reg .pred p;\nelect.sync _|p, 0xffffffff;\n@p mbarrier.arrive.shared::cta.b64 _, [%0];\n}" ::"r"(bar) : "memory");
}
__device__ __forceinline__ void load_wo_elect(const Maps& mp, int branchB, int nt, int c) {
    constexpr uint32_t sb = SM_BASE;
    const CUtensorMap* tm = branchB ? &mp.woB : &mp.woA;
    asm volatile(
        "{.reg .pred p;\n"
        "elect.sync _|p, 0xffffffff;\n"
        "@p mbarrier.arrive.expect_tx.shared::cta.b64 _, [%0], 16384;\n"
        "@p cp.async.bulk.tensor.2d.shared::cluster.global.mbarrier::complete_tx::bytes [%1], [%3, {%4, %6}], [%0];\n"
        "@p cp.async.bulk.tensor.2d.shared::cluster.global.mbarrier::complete_tx::bytes [%2], [%3, {%5, %6}], [%0];\n"
        "}" ::"r"(sb + B_WFULL + 8 * c), "r"(sb + AT_K + c * 8192), "r"(sb + AT_V + c * 8192), "l"(tm), "r"(nt * 128), "r"(nt * 128 + 64), "r"(c * 64)
        : "memory");
}
__device__ __forceinline__ void load_kv_elect(int h, int c) {
    constexpr uint32_t sb = SM_BASE;
    asm volatile(
        "{.reg .pred p;\n"
        "elect.sync _|p, 0xffffffff;\n"
        "@p mbarrier.arrive.expect_tx.shared::cta.b64 _, [%0], 16384;\n"
        "@p cp.async.bulk.shared::cluster.global.mbarrier::complete_tx::bytes [%1], [%3], 8192, [%0];\n"
        "@p cp.async.bulk.shared::cluster.global.mbarrier::complete_tx::bytes [%2], [%4], 8192, [%0];\n"
        "}" ::"r"(sb + B_KV + 8 * c), "r"(sb + AT_K + c * 8192), "r"(sb + AT_V + c * 8192),
        "l"(g_kB + ((size_t)h * S_LEN + c * 256) * 16), "l"(g_vB + ((size_t)h * S_LEN + c * 256) * 16) : "memory");
}
__device__ __forceinline__ void load_wo(const Maps& mp, int branchB, int nt, int c) {
    constexpr uint32_t sb = SM_BASE;
    const CUtensorMap* tm = branchB ? &mp.woB : &mp.woA;
    mbar_expect_tx(sb + B_WFULL + 8 * c, 16384);
    tma_load_2d(sb + AT_K + c * 8192, tm, nt * 128, c * 64, sb + B_WFULL + 8 * c);
    tma_load_2d(sb + AT_V + c * 8192, tm, nt * 128 + 64, c * 64, sb + B_WFULL + 8 * c);
}

__device__ __forceinline__ void phase_attn(uint8_t* smem, const Maps& mp) {
    constexpr uint32_t sb = SM_BASE;
    const int tid = threadIdx.x, warp = (tid >> 5) & 3, lane = tid & 31;
    const int wg = __shfl_sync(0xffffffffu, tid >> 7, 0);
    const int wwarp = __shfl_sync(0xffffffffu, warp, 0);
    const int h = blockIdx.x >> 2, qb = blockIdx.x & 3;
    constexpr int NCH = 8;
    constexpr uint32_t sK = sb + AT_K, sV = sb + AT_V, sQ = sb + AT_Q, sBar = sb + B_KV;

    named_bar(4 + wg, 128);
    mbar_wait(sb + B_TAB, 0);
    mbar_wait(sb + B_Q, 0);
    if (wg >= 2) {
        named_bar(2, 256);
        if (wwarp < 3) load_kv_elect(h, 2 + (wg - 2) * 3 + wwarp);
    }
    __syncwarp();
    STAMP(1, 2);
    bool safe;
    {
        const float* nrm = (const float*)(smem + OFF_NORM);
        const float qv = lane < 4 ? nrm[qb * 4 + lane] : 0.f;
        const float kv = lane < 16 ? nrm[16 + lane] : 0.f;
        const uint32_t qm = __reduce_max_sync(0xffffffffu, __float_as_uint(qv));
        const uint32_t km = __reduce_max_sync(0xffffffffu, __float_as_uint(kv));
        safe = (__uint_as_float(qm) * __uint_as_float(km) * (16.f * 1.05f) < AT_SAFE2);
    }
    const uint64_t dK0 = mk_desc(DESC_SW32, sK, 16, 256);
    const uint64_t dC = mk_desc(DESC_SW32, sb + AT_CT, 16, 0);
    const uint64_t dV0 = mk_desc(DESC_SW32, sV, AT_ONES - AT_V, 256);
    constexpr int64_t VSTEP = 32 - (32 << 16);
    const uint32_t lane4 = lane * 4;
    uint32_t aone[4];
    asm volatile("ld.shared.v4.u32 {%0,%1,%2,%3}, [%4];" : "=r"(aone[0]), "=r"(aone[1]), "=r"(aone[2]), "=r"(aone[3]) : "r"(sb + AT_CT + 256 + ((lane & 3) == 0 ? 0 : 16)));
    const int g = lane >> 2, t = lane & 3;
    constexpr int NT = AT_NT, NP = AT_NP;
    const int oBranch = blockIdx.x >> 6, oNt = blockIdx.x & 3;

    STAMP(1, 3);
#pragma unroll 1
    for (int qi = 0; qi < 2; qi++) {
        const int qt = wg * 2 + qi;
        const int row0 = qb * 512 + qt * 64 + warp * 16;
        uint32_t qa[4];
        ldsm_x4(sQ + (qt * 64 + warp * 16 + (lane & 7) + ((lane >> 3) & 1) * 8) * 32 + ((((lane >> 4) ^ ((lane & 7) >> 2))) << 4), qa);
        float o[12], s[NT / 2];
#pragma unroll
        for (int i = 0; i < 12; i++) o[i] = 0.f;
#pragma unroll
        for (int i = 0; i < NT / 2; i++) s[i] = 0.f;
        fence_regs(o); fence_regs(s);
        if (safe) {
            uint32_t pa[NT / 4], pb[NT / 4];
            auto issue_qk = [&](uint64_t dK, int np) {
                wgmma_rs_n64<0>(s, qa, dK);
                if (np == 24) wgmma_rs_n24<1>(s, aone, dC); else if (np == 32) wgmma_rs_n32<1>(s, aone, dC); else wgmma_rs_n40<1>(s, aone, dC);
            };
            mbar_wait(sBar, 0);
            wg_fence();
            issue_qk(dK0, NP);
            wg_commit();
            wg_wait<0>();
            fence_regs(s);
            att_exp<NT, NP>(s, pa, lane4);
            if (qi == 0 && wg == 2 && wwarp == 0) {
                asm volatile("{.reg .pred p;\nelect.sync _|p, 0xffffffff;\n@p red.release.gpu.global.add.s32 [%0], 1;\n}" ::"l"(&g_cnt.qkvA[blockIdx.x & 7]) : "memory");
            }
            uint64_t dK = dK0, dV = dV0;
            auto step = [&](uint32_t (&pc)[NT / 4], uint32_t (&pn)[NT / 4], bool last, int jt) {
                wg_fence();
                if (!last) { issue_qk(dK + (uint64_t)(jt * NT * 2 + NT * 2), (jt & 1) ? NP : AT_NP2); wg_commit(); }
#pragma unroll
                for (int kk = 0; kk < NT / 16; kk++) wgmma_rs_n24_tb<1>(o, pc + kk * 4, dV + (uint64_t)((int64_t)(jt * (NT / 16) + kk) * VSTEP));
                wg_commit();
                if (!last) {
                    wg_wait<1>();
                    fence_regs(s);
                    if (jt & 1) att_exp<NT, NP>(s, pn, lane4); else att_exp<NT, AT_NP2>(s, pn, lane4);
                }
                if (last || jt == 3) { wg_wait<0>(); fence_regs(pc); fence_regs(o); }
            };
            constexpr int TPC = 256 / NT;
#pragma unroll 1
            for (int cch = 0; cch < NCH; cch++) {
#pragma unroll
                for (int jj = 0; jj < TPC; jj += 2) {
                    step(pa, pb, false, jj);
                    if (jj + 2 == TPC) {
                        if (cch == NCH - 1) break;
                        mbar_wait(sBar + 8 * (cch + 1), 0);
                    }
                    step(pb, pa, false, jj + 1);
                }
                dK += 256 * 2; dV += (uint64_t)(16 * VSTEP);
                if (qi == 1 && wwarp == 0 && cch < NCH - 1) {
                    mbar_arrive_elect(sb + B_CONS + 8 * cch);
                    if (cch >= 1 && wg == ((cch - 1) & 3)) { mbar_wait(sb + B_CONS + 8 * (cch - 1), 0); load_wo_elect(mp, oBranch, oNt, cch - 1); }
                }
            }
            dV -= (uint64_t)(16 * VSTEP);
            step(pb, pa, true, TPC - 1);
            if (qi == 1 && wwarp == 0) {
                mbar_arrive_elect(sb + B_CONS + 8 * 7);
                if (wg == 2) { mbar_wait(sb + B_CONS + 8 * 6, 0); load_wo_elect(mp, oBranch, oNt, 6); }
                if (wg == 3) { mbar_wait(sb + B_CONS + 8 * 7, 0); load_wo_elect(mp, oBranch, oNt, 7); }
            }
        } else {
            if (qi == 0 && tid == 256) signal_add(&g_cnt.qkvA[blockIdx.x & 7]);
            float m0 = -INFINITY, m1 = -INFINITY;
            uint32_t p[NT / 4];
#pragma unroll 1
            for (int j = 0; j < S_LEN / NT; j++) {
                if ((j * NT) % 256 == 0) mbar_wait(sBar + 8 * ((j * NT) / 256), 0);
                wg_fence();
                wgmma_rs_n64<0>(s, qa, dK0 + (uint64_t)(j * NT * 2));
                wg_commit();
                wg_wait<0>();
                fence_regs(s); fence_regs(o);
                float t0 = m0, t1 = m1;
#pragma unroll
                for (int i = 0; i < NT / 2; i += 4) { t0 = fmaxf(t0, fmaxf(s[i], s[i + 1])); t1 = fmaxf(t1, fmaxf(s[i + 2], s[i + 3])); }
                t0 = fmaxf(t0, __shfl_xor_sync(0xffffffffu, t0, 1)); t0 = fmaxf(t0, __shfl_xor_sync(0xffffffffu, t0, 2));
                t1 = fmaxf(t1, __shfl_xor_sync(0xffffffffu, t1, 1)); t1 = fmaxf(t1, __shfl_xor_sync(0xffffffffu, t1, 2));
                const float r0 = ex2f(m0 - t0), r1 = ex2f(m1 - t1);
                m0 = t0; m1 = t1;
#pragma unroll
                for (int i = 0; i < 12; i += 4) { o[i] *= r0; o[i + 1] *= r0; o[i + 2] *= r1; o[i + 3] *= r1; }
#pragma unroll
                for (int i = 0; i < NT / 4; i += 2) {
                    p[i] = pack_bf16(ex2f(s[2 * i] - m0), ex2f(s[2 * i + 1] - m0));
                    p[i + 1] = pack_bf16(ex2f(s[2 * i + 2] - m1), ex2f(s[2 * i + 3] - m1));
                }
                fence_regs(o);
                wg_fence();
#pragma unroll
                for (int kk = 0; kk < NT / 16; kk++) wgmma_rs_n24_tb<1>(o, p + kk * 4, dV0 + (uint64_t)((int64_t)(j * (NT / 16) + kk) * VSTEP));
                wg_commit();
                wg_wait<0>();
                fence_regs(p);
            }
            fence_regs(o);
        }
        const float l0 = 1.f / o[8], l1 = 1.f / o[10];
        uint32_t* op0 = (uint32_t*)(g_o + (size_t)(row0 + g) * 1024 + 512 + h * 16);
        uint32_t* op1 = (uint32_t*)(g_o + (size_t)(row0 + g + 8) * 1024 + 512 + h * 16);
        op0[t] = pack_bf16(o[0] * l0, o[1] * l0);
        op0[4 + t] = pack_bf16(o[4] * l0, o[5] * l0);
        op1[t] = pack_bf16(o[2] * l1, o[3] * l1);
        op1[4 + t] = pack_bf16(o[6] * l1, o[7] * l1);
    }
    named_bar(4 + wg, 128);
    if ((tid & 127) == 0) signal_add(&g_cnt.oB[(qb * 4 + wg) * 8 + (h >> 2)]);
    STAMP(1, 4);
    __syncthreads();
    if (!safe && tid == 0) {
        for (int c = 0; c < 8; c++) load_wo(mp, oBranch, oNt, c);
    }
}

__device__ __forceinline__ void phase_out(uint8_t* smem, const Maps& mp) {
    (void)smem;
    constexpr uint32_t sb = SM_BASE;
    const int tid = threadIdx.x, warp = tid >> 5, lane = tid & 31;
    const int branchB = blockIdx.x >> 6;
    const int mt = (blockIdx.x & 63) >> 2, nt = blockIdx.x & 3;
    const int wg = __shfl_sync(0xffffffffu, warp >> 2, 0);
    if (wg == 2) {
        if (tid < 256 + 32) {
            if (lane == 0) { tma_prefetch_desc(&mp.o); tma_prefetch_desc(&mp.out); }
            const int* cnt = branchB ? &g_cnt.oB[mt * 8 + (lane & 7)] : &g_cnt.oA;
            int next = 0, spins = 0;
            while (next < 8) {
                int v;
                asm volatile("ld.acquire.gpu.global.s32 %0, [%1];" : "=r"(v) : "l"(cnt) : "memory");
                const uint32_t ready = __ballot_sync(0xffffffffu, v >= 4);
                __syncwarp();
                if (lane == 0) {
                    fence_async_all();
                    for (int kb = next; kb < 8 && ((ready >> kb) & 1); kb++) {
                        const int s = kb & 3;
                        if (kb >= 4) mbar_wait(sb + B_OEMPTY + 8 * s, 0);
                        mbar_expect_tx(sb + B_OFULL + 8 * s, 16384);
                        tma_load_2d(sb + P3_O + s * 16384, &mp.o, branchB * 512 + kb * 64, mt * 128, sb + B_OFULL + 8 * s);
                    }
                }
                while (next < 8 && ((ready >> next) & 1)) next++;
                __syncwarp();
                if (++spins > (1 << 22)) __trap();
                if (next < 8) __nanosleep(SPIN_NS);
            }
            if (lane == 0) finish_ticket();
        }
        return;
    }
    if (wg == 3) return;
    float acc[64];
#pragma unroll
    for (int i = 0; i < 64; i++) acc[i] = 0.f;
    fence_regs(acc);
    const uint64_t dA0 = mk_desc(DESC_SW128, sb + P3_O + wg * 8192, 16, 1024);
#pragma unroll
    for (int kb = 0; kb < 8; kb++) {
        const int s = kb & 3;
        mbar_wait(sb + B_WFULL + 8 * kb, 0);
        mbar_wait(sb + B_OFULL + 8 * s, kb >> 2);
        if (kb == 0) STAMP(2, 2);
        const uint64_t dA = dA0 + (uint64_t)(s * (16384 >> 4));
        const uint64_t dB = mk_desc(DESC_SW128, sb + AT_K + kb * 8192, AT_V - AT_K, 1024);
        wg_fence();
#pragma unroll
        for (int k = 0; k < 4; k++) wgmma_ss_n128_tb(acc, dA + k * 2, dB + k * 128, 1);
        wg_commit();
        if (kb >= 1 && kb <= 4) {
            wg_wait<1>();
            if ((tid & 127) == 0) mbar_arrive(sb + B_OEMPTY + 8 * (kb - 1));
        }
    }
    wg_wait<0>();
    fence_regs(acc);
    STAMP(2, 3);
    const int wq = warp & 3;
    const uint32_t stg = sb + P3_O + wg * 8192;
    const int lr = wq * 16 + (lane & 7) + ((lane >> 3) & 1) * 8, lc = lane >> 4;
#pragma unroll
    for (int j = 0; j < 8; j++) {
        const float* a = acc + j * 8;
        const int chunk = (j & 3) * 2 + lc;
        stsm_x4(stg + (j >> 2) * 16384 + lr * 128 + ((chunk ^ (lr & 7)) << 4),
                pack_bf16(a[0], a[1]), pack_bf16(a[2], a[3]), pack_bf16(a[4], a[5]), pack_bf16(a[6], a[7]));
    }
    fence_async_smem();
    named_bar(4 + wg, 128);
    if ((tid & 127) < 2) {
        const int j = tid & 1;
        tma_store_2d(&mp.out, stg + j * 16384, branchB * 512 + nt * 128 + j * 64, mt * 128 + wg * 64);
        bulk_commit();
        asm volatile("cp.async.bulk.wait_group.read 0;" ::: "memory");
    }
    STAMP(2, 4);
}

__device__ __noinline__ void linattn_mid(uint8_t* smem, int cta, const CUtensorMap* tmO16) {
    constexpr uint32_t sb = SM_BASE;
    const int tid = threadIdx.x, warp = tid >> 5, lane = tid & 31;
    constexpr int NBUF = 4;
    const uint32_t sBar = sb;
    const uint32_t sQ0 = sb + 1024;
    const uint32_t sSt = sQ0 + NBUF * 32768;
    float* skv = (float*)(smem + 1024 + NBUF * 32768 + 65536);
    if (tid == 0) { for (int i = 0; i < NBUF; i++) { mbar_init(sBar + 8 * i, 1); mbar_init(sBar + 64 + 8 * i, 16); } fence_mbar_init(); }
    __syncthreads();
    if (warp == 0 && lane == 0) { spin_ge(&g_cnt.qkvA[2 * cta], 16); spin_ge(&g_cnt.qkvA[2 * cta + 1], 16); }
    __syncthreads();
    if (lane == 0) fence_async_all();
    __syncwarp();
    STAMP(1, 2);
    auto load_chunk = [&](int c, int j) {
        bulk_g2s(sQ0 + (c % NBUF) * 32768 + j * 8192, g_qA + ((size_t)(cta * 8 + (c >> 3) * 4 + j) * S_LEN + (c & 7) * 256) * 16, 8192, sBar + 8 * (c % NBUF));
    };
    if (lane == 0 && warp < NBUF) {
        mbar_expect_tx(sBar + 8 * warp, 32768);
        for (int j = 0; j < 4; j++) load_chunk(warp, j);
    }
    {
        const int hh = tid >> 6, e = tid & 63;
        const float* gp = g_kvp + (size_t)(cta * 8 + hh) * 272 + e * 4;
        const float* gz = g_kvp + (size_t)(cta * 8 + ((tid >> 4) & 7)) * 272 + 256 + (tid & 15);
        float4 v0, v1, v2, v3, v4, v5, v6, v7;
        float z[16];
#define LD4(m) (*(const float4*)(gp + (size_t)(m) * NH * 272))
#define ADD4(a, b) (a).x += (b).x, (a).y += (b).y, (a).z += (b).z, (a).w += (b).w
        if (tid < 128) {
#pragma unroll
            for (int m = 0; m < 16; m++) z[m] = gz[(size_t)m * NH * 272];
        }
        v0 = LD4(0); v1 = LD4(1); v2 = LD4(2); v3 = LD4(3); v4 = LD4(4); v5 = LD4(5); v6 = LD4(6); v7 = LD4(7);
        {
            const float4 w0 = LD4(8), w1 = LD4(9), w2 = LD4(10), w3 = LD4(11), w4 = LD4(12), w5 = LD4(13), w6 = LD4(14), w7 = LD4(15);
            ADD4(v0, w0); ADD4(v1, w1); ADD4(v2, w2); ADD4(v3, w3); ADD4(v4, w4); ADD4(v5, w5); ADD4(v6, w6); ADD4(v7, w7);
        }
        ADD4(v0, v4); ADD4(v1, v5); ADD4(v2, v6); ADD4(v3, v7); ADD4(v0, v2); ADD4(v1, v3); ADD4(v0, v1);
#undef LD4
#undef ADD4
        *(float4*)(skv + hh * 272 + e * 4) = v0;
        if (tid < 128) {
#pragma unroll
            for (int w = 8; w > 0; w >>= 1) {
#pragma unroll
                for (int m = 0; m < w; m++) z[m] += z[m + w];
            }
            skv[((tid >> 4) & 7) * 272 + 256 + (tid & 15)] = z[0];
        }
    }
    __syncthreads();
    STAMP(1, 3);
    if (tid == 511) finish_ticket();
    const int g = lane >> 2, t = lane & 3;
    const int lr = (lane & 7) + ((lane >> 3) & 1) * 8, lc = lane >> 4;
    const uint32_t loff = (warp * 16 + lr) * 32 + ((lc ^ ((lr & 7) >> 2)) << 4);
#pragma unroll 1
    for (int quad = 0; quad < 2; quad++) {
        uint32_t bf[4][6];
#pragma unroll
        for (int j = 0; j < 4; j++) {
            const float* kv = skv + (quad * 4 + j) * 272;
            bf[j][0] = pack_bf16(kv[(2 * t) * 16 + g], kv[(2 * t + 1) * 16 + g]);
            bf[j][1] = pack_bf16(kv[(2 * t + 8) * 16 + g], kv[(2 * t + 9) * 16 + g]);
            bf[j][2] = pack_bf16(kv[(2 * t) * 16 + 8 + g], kv[(2 * t + 1) * 16 + 8 + g]);
            bf[j][3] = pack_bf16(kv[(2 * t + 8) * 16 + 8 + g], kv[(2 * t + 9) * 16 + 8 + g]);
            bf[j][4] = pack_bf16(kv[256 + 2 * t], kv[256 + 2 * t + 1]);
            bf[j][5] = pack_bf16(kv[256 + 2 * t + 8], kv[256 + 2 * t + 9]);
        }
#pragma unroll 1
        for (int rc = 0; rc < 8; rc++) {
            const int c = quad * 8 + rc;
            mbar_wait(sBar + 8 * (c % NBUF), (c / NBUF) & 1);
            const uint32_t qb = sQ0 + (c % NBUF) * 32768 + loff;
            const uint32_t stg = sSt + (c & 1) * 32768 + warp * 2048;
            uint32_t a[4][4];
#pragma unroll
            for (int j = 0; j < 4; j++) ldsm_x4(qb + j * 8192, a[j]);
            __syncwarp();
            if (lane == 0) {
                mbar_arrive(sBar + 64 + 8 * (c % NBUF));
                if (c >= 1 && warp == (c & 15) && c - 1 + NBUF < 16) {
                    const int cp = c - 1;
                    mbar_wait(sBar + 64 + 8 * (cp % NBUF), (cp / NBUF) & 1);
                    mbar_expect_tx(sBar + 8 * (cp % NBUF), 32768);
                    for (int j = 0; j < 4; j++) load_chunk(cp + NBUF, j);
                }
                if (c >= 2) asm volatile("cp.async.bulk.wait_group.read 1;" ::: "memory");
            }
            __syncwarp();
#pragma unroll
            for (int j = 0; j < 4; j++) {
#pragma unroll
                for (int i = 0; i < 4; i++) a[j][i] = phi_bf16x2(a[j][i]);
                float n0[4] = {0.f, 0.f, 0.f, 0.f}, n1[4] = {0.f, 0.f, 0.f, 0.f}, dn[4] = {0.f, 0.f, 0.f, 0.f};
                mma_bf16(n0, a[j], bf[j][0], bf[j][1]);
                mma_bf16(n1, a[j], bf[j][2], bf[j][3]);
                mma_bf16(dn, a[j], bf[j][4], bf[j][5]);
                const float i0 = rcp_fast(dn[0] + 1e-6f), i1 = rcp_fast(dn[2] + 1e-6f);
                stsm_x4(stg + lr * 128 + (((j * 2 + lc) ^ (lr & 7)) << 4),
                        pack_bf16(n0[0] * i0, n0[1] * i0), pack_bf16(n0[2] * i1, n0[3] * i1),
                        pack_bf16(n1[0] * i0, n1[1] * i0), pack_bf16(n1[2] * i1, n1[3] * i1));
            }
            fence_async_smem();
            __syncwarp();
            if (lane == 0) {
                tma_store_2d(tmO16, stg, cta * 128 + quad * 64, rc * 256 + warp * 16);
                bulk_commit();
            }
        }
    }
    if (lane == 0) { bulk_wait0(); fence_async_all(); }
    __syncthreads();
    if (tid == 0) signal_add(&g_cnt.oA);
    STAMP(1, 5);
}

__global__ void __launch_bounds__(512, 1) fused_kernel(const __grid_constant__ Maps mp) {
    extern __shared__ __align__(1024) uint8_t smem[];
    if (smem_u32(smem) != SM_BASE) __trap();
    STAMP(0, 0);
    if (blockIdx.x >= 128) {
        linattn_mid(smem, blockIdx.x - 128, &mp.o16);
    } else {
        phase_qkv(smem, mp);
        STAMP(1, 1);
        phase_attn(smem, mp);
        phase_out(smem, mp);
    }
}

typedef CUresult (*EncodeFn)(CUtensorMap*, CUtensorMapDataType, cuuint32_t, void*, const cuuint64_t*, const cuuint64_t*,
                             const cuuint32_t*, const cuuint32_t*, CUtensorMapInterleave, CUtensorMapSwizzle,
                             CUtensorMapL2promotion, CUtensorMapFloatOOBfill);

void make_map(EncodeFn enc, CUtensorMap* tm, const void* ptr, uint64_t cols, uint64_t rows, uint32_t boxc, uint32_t boxr) {
    cuuint64_t dims[2] = {cols, rows};
    cuuint64_t strides[1] = {cols * 2};
    cuuint32_t box[2] = {boxc, boxr};
    cuuint32_t es[2] = {1, 1};
    enc(tm, CU_TENSOR_MAP_DATA_TYPE_BFLOAT16, 2, const_cast<void*>(ptr), dims, strides, box, es, CU_TENSOR_MAP_INTERLEAVE_NONE,
        CU_TENSOR_MAP_SWIZZLE_128B, CU_TENSOR_MAP_L2_PROMOTION_L2_256B, CU_TENSOR_MAP_FLOAT_OOB_FILL_NONE);
}

struct HostState {
    bool init;
    const void* key[7];
    Maps mp;
};
HostState g_hs;

}

extern "C" void kernel_launch(void* const* d_in, const int* in_sizes, int n_in, void* d_out, int out_size) {
    (void)in_sizes; (void)n_in; (void)out_size;
    HostState& hs = g_hs;
    bool same = hs.init && hs.key[6] == d_out;
    for (int i = 0; i < 6 && same; i++) same = hs.key[i] == d_in[i];
    if (!same) {
        void* fn = nullptr;
        cudaDriverEntryPointQueryResult qr;
        cudaGetDriverEntryPoint("cuTensorMapEncodeTiled", &fn, cudaEnableDefault, &qr);
        EncodeFn enc = (EncodeFn)fn;
        void* po = nullptr;
        cudaGetSymbolAddress(&po, g_o);
        make_map(enc, &hs.mp.xA, d_in[0], 512, 2048, 64, 128);
        make_map(enc, &hs.mp.wA, d_in[1], 1536, 512, 64, 64);
        make_map(enc, &hs.mp.woA, d_in[2], 512, 512, 64, 64);
        make_map(enc, &hs.mp.xB, d_in[3], 512, 2048, 64, 128);
        make_map(enc, &hs.mp.wB, d_in[4], 1536, 512, 64, 64);
        make_map(enc, &hs.mp.woB, d_in[5], 512, 512, 64, 64);
        make_map(enc, &hs.mp.o, po, 1024, 2048, 64, 128);
        make_map(enc, &hs.mp.o16, po, 1024, 2048, 64, 16);
        make_map(enc, &hs.mp.out, d_out, 1024, 2048, 64, 64);
        cudaFuncSetAttribute(fused_kernel, cudaFuncAttributeMaxDynamicSharedMemorySize, SMEM_BYTES);
        for (int i = 0; i < 6; i++) hs.key[i] = d_in[i];
        hs.key[6] = d_out;
        hs.init = true;
    }
    fused_kernel<<<132, 512, SMEM_BYTES, cudaStreamPerThread>>>(hs.mp);
}
```

```cpp
#include <cuda_runtime.h>
#include <cuda_bf16.h>
#include <cuda.h>
#include <stdint.h>

namespace {

constexpr int S_LEN = 2048;
constexpr int NH = 32;

__device__ __align__(1024) uint16_t g_qB[NH * S_LEN * 16];
__device__ __align__(1024) uint16_t g_kB[NH * S_LEN * 16];
__device__ __align__(1024) uint16_t g_vB[NH * S_LEN * 16];
__device__ __align__(1024) uint16_t g_qA[NH * S_LEN * 16];
__device__ __align__(1024) uint16_t g_o[S_LEN * 1024];
__device__ __align__(16) float g_kvp[16 * NH * 272];
__device__ __align__(64) float g_qn[NH * 16];
__device__ __align__(64) float g_kn[NH * 16];

struct Counters {
    int qkvB[8];
    int qkvA[8];
    int oB[16 * 8];
    int oA;
    int done;
};
__device__ Counters g_cnt;


__device__ __forceinline__ uint32_t smem_u32(const void* p) { return (uint32_t)__cvta_generic_to_shared(p); }
__device__ __forceinline__ void wg_fence() { asm volatile("wgmma.fence.sync.aligned;" ::: "memory"); }
__device__ __forceinline__ void wg_commit() { asm volatile("wgmma.commit_group.sync.aligned;" ::: "memory"); }
template <int N> __device__ __forceinline__ void wg_wait() { asm volatile("wgmma.wait_group.sync.aligned %0;" ::"n"(N) : "memory"); }
__device__ __forceinline__ void mbar_init(uint32_t bar, uint32_t cnt) { asm volatile("mbarrier.init.shared::cta.b64 [%0], %1;" ::"r"(bar), "r"(cnt)); }
__device__ __forceinline__ void mbar_expect_tx(uint32_t bar, uint32_t bytes) {
    asm volatile("mbarrier.arrive.expect_tx.shared::cta.b64 _, [%0], %1;" ::"r"(bar), "r"(bytes) : "memory");
}
__device__ __forceinline__ void mbar_wait(uint32_t bar, uint32_t parity) {
    asm volatile(
        "{.reg .pred p, q;\n"
        ".reg .u32 n;\n"
        "mbarrier.try_wait.parity.shared::cta.b64 p, [%0], %1;\n"
        "@p bra WAIT_DONE;\n"
        "mov.u32 n, 0;\n"
        "WAIT_LOOP:\n"
        "mbarrier.try_wait.parity.shared::cta.b64 p, [%0], %1;\n"
        "@p bra WAIT_DONE;\n"
        "add.u32 n, n, 1;\n"
        "setp.lt.u32 q, n, 0x400000;\n"
        "@q bra WAIT_LOOP;\n"
        "trap;\n"
        "WAIT_DONE:\n}" ::"r"(bar), "r"(parity) : "memory");
}
__device__ __forceinline__ void mbar_arrive(uint32_t bar) { asm volatile("mbarrier.arrive.shared::cta.b64 _, [%0];" ::"r"(bar) : "memory"); }
__device__ __forceinline__ void fence_mbar_init() { asm volatile("fence.mbarrier_init.release.cluster;" ::: "memory"); }
__device__ __forceinline__ void fence_async_smem() { asm volatile("fence.proxy.async.shared::cta;" ::: "memory"); }
constexpr int SPIN_NS = 100;
__device__ __forceinline__ void spin_ge(const int* p, int target) {
    int it = 0;
    while (true) {
        int v;
        asm volatile("ld.acquire.gpu.global.s32 %0, [%1];" : "=r"(v) : "l"(p) : "memory");
        if (v >= target) break;
        if (++it > (1 << 22)) __trap();
        __nanosleep(SPIN_NS);
    }
}
__device__ __forceinline__ void finish_ticket() {
    if (atomicAdd(&g_cnt.done, 1) == (int)gridDim.x - 1) {
        int* c = (int*)&g_cnt;
        for (int i = 0; i < (int)(sizeof(Counters) / sizeof(int)); i++) c[i] = 0;
    }
}
__device__ __forceinline__ void signal_add(int* p) { asm volatile("red.release.gpu.global.add.s32 [%0], 1;" ::"l"(p) : "memory"); }
__device__ __forceinline__ void fence_async_all() { asm volatile("fence.proxy.async.global;" ::: "memory"); }
__device__ __forceinline__ void named_bar(int id, int n) { asm volatile("bar.sync %0, %1;" ::"r"(id), "r"(n) : "memory"); }

__device__ __forceinline__ void bulk_g2s(uint32_t dst, const void* src, uint32_t bytes, uint32_t bar) {
    asm volatile("cp.async.bulk.shared::cluster.global.mbarrier::complete_tx::bytes [%0], [%1], %2, [%3];" ::"r"(dst), "l"(src), "r"(bytes), "r"(bar) : "memory");
}
__device__ __forceinline__ void bulk_commit() { asm volatile("cp.async.bulk.commit_group;" ::: "memory"); }
__device__ __forceinline__ void bulk_wait0() { asm volatile("cp.async.bulk.wait_group 0;" ::: "memory"); }
__device__ __forceinline__ void tma_load_2d(uint32_t dst, const CUtensorMap* tm, int c0, int c1, uint32_t bar) {
    asm volatile("cp.async.bulk.tensor.2d.shared::cluster.global.mbarrier::complete_tx::bytes [%0], [%1, {%3, %4}], [%2];" ::"r"(dst), "l"(tm), "r"(bar), "r"(c0), "r"(c1) : "memory");
}
__device__ __forceinline__ void tma_store_2d(const CUtensorMap* tm, uint32_t src, int c0, int c1) {
    asm volatile("cp.async.bulk.tensor.2d.global.shared::cta.bulk_group [%0, {%2, %3}], [%1];" ::"l"(tm), "r"(src), "r"(c0), "r"(c1) : "memory");
}
__device__ __forceinline__ void tma_prefetch_desc(const CUtensorMap* tm) { asm volatile("prefetch.tensormap [%0];" ::"l"(tm) : "memory"); }

__device__ __forceinline__ uint32_t pack_bf16(float lo, float hi) {
    uint32_t r; asm("cvt.rn.bf16x2.f32 %0, %1, %2;" : "=r"(r) : "f"(hi), "f"(lo)); return r;
}
__device__ __forceinline__ float ex2f(float x) { float r; asm("ex2.approx.ftz.f32 %0, %1;" : "=f"(r) : "f"(x)); return r; }
__device__ __forceinline__ float bf_lo(uint32_t p) { return __uint_as_float(p << 16); }
__device__ __forceinline__ float bf_hi(uint32_t p) { return __uint_as_float(p & 0xFFFF0000u); }
__device__ __forceinline__ void stsm_x4(uint32_t addr, uint32_t r0, uint32_t r1, uint32_t r2, uint32_t r3) {
    asm volatile("stmatrix.sync.aligned.m8n8.x4.shared.b16 [%0], {%1,%2,%3,%4};" ::"r"(addr), "r"(r0), "r"(r1), "r"(r2), "r"(r3) : "memory");
}
__device__ __forceinline__ void ldsm_x4(uint32_t addr, uint32_t* r) {
    asm volatile("ldmatrix.sync.aligned.m8n8.x4.shared.b16 {%0,%1,%2,%3}, [%4];" : "=r"(r[0]), "=r"(r[1]), "=r"(r[2]), "=r"(r[3]) : "r"(addr) : "memory");
}
__device__ __forceinline__ void ldsm_x4_t(uint32_t addr, uint32_t* r) {
    asm volatile("ldmatrix.sync.aligned.m8n8.x4.trans.shared.b16 {%0,%1,%2,%3}, [%4];" : "=r"(r[0]), "=r"(r[1]), "=r"(r[2]), "=r"(r[3]) : "r"(addr) : "memory");
}
__device__ __forceinline__ void mma_bf16(float* d, const uint32_t* a, uint32_t b0, uint32_t b1) {
    asm volatile("mma.sync.aligned.m16n8k16.row.col.f32.bf16.bf16.f32 {%0,%1,%2,%3}, {%4,%5,%6,%7}, {%8,%9}, {%0,%1,%2,%3};"
                 : "+f"(d[0]), "+f"(d[1]), "+f"(d[2]), "+f"(d[3]) : "r"(a[0]), "r"(a[1]), "r"(a[2]), "r"(a[3]), "r"(b0), "r"(b1));
}
__device__ __forceinline__ uint32_t phi_bf16x2(uint32_t p) {
    const float t0 = bf_lo(p), t1 = bf_hi(p);
    const float a0 = fmaf(t0 + fabsf(t0), 0.5f, ex2f((t0 - fabsf(t0)) * 0.7213475204444817f));
    const float a1 = fmaf(t1 + fabsf(t1), 0.5f, ex2f((t1 - fabsf(t1)) * 0.7213475204444817f));
    const uint32_t a = pack_bf16(a0, a1);
    uint32_t r;
    asm("add.rn.bf16x2 %0, %1, %2;" : "=r"(r) : "r"(a), "r"(0x35863586u));
    return r;
}
__device__ __forceinline__ float rcp_fast(float x) { float r; asm("rcp.approx.ftz.f32 %0, %1;" : "=f"(r) : "f"(x)); return r; }
template <typename T, int N> __device__ __forceinline__ void fence_regs(T (&r)[N]) {
#pragma unroll
    for (int i = 0; i < N; i++) {
        if constexpr (sizeof(T) == 4 && T(0.5) != T(0)) asm volatile("" : "+f"(r[i])::"memory");
        else asm volatile("" : "+r"(r[i])::"memory");
    }
}

__device__ __forceinline__ void wgmma_ss_n192_tb(float* d, uint64_t da, uint64_t db, int sd) {
  asm volatile("{.reg .pred p; setp.ne.b32 p, %98, 0; wgmma.mma_async.sync.aligned.m64n192k16.f32.bf16.bf16 {%0,%1,%2,%3,%4,%5,%6,%7,%8,%9,%10,%11,%12,%13,%14,%15,%16,%17,%18,%19,%20,%21,%22,%23,%24,%25,%26,%27,%28,%29,%30,%31,%32,%33,%34,%35,%36,%37,%38,%39,%40,%41,%42,%43,%44,%45,%46,%47,%48,%49,%50,%51,%52,%53,%54,%55,%56,%57,%58,%59,%60,%61,%62,%63,%64,%65,%66,%67,%68,%69,%70,%71,%72,%73,%74,%75,%76,%77,%78,%79,%80,%81,%82,%83,%84,%85,%86,%87,%88,%89,%90,%91,%92,%93,%94,%95}, %96, %97, p, 1, 1, 0, 1;}"
    : "+f"(d[0]), "+f"(d[1]), "+f"(d[2]), "+f"(d[3]), "+f"(d[4]), "+f"(d[5]), "+f"(d[6]), "+f"(d[7]), "+f"(d[8]), "+f"(d[9]), "+f"(d[10]), "+f"(d[11]), "+f"(d[12]), "+f"(d[13]), "+f"(d[14]), "+f"(d[15]), "+f"(d[16]), "+f"(d[17]), "+f"(d[18]), "+f"(d[19]), "+f"(d[20]), "+f"(d[21]), "+f"(d[22]), "+f"(d[23]), "+f"(d[24]), "+f"(d[25]), "+f"(d[26]), "+f"(d[27]), "+f"(d[28]), "+f"(d[29]), "+f"(d[30]), "+f"(d[31]), "+f"(d[32]), "+f"(d[33]), "+f"(d[34]), "+f"(d[35]), "+f"(d[36]), "+f"(d[37]), "+f"(d[38]), "+f"(d[39]), "+f"(d[40]), "+f"(d[41]), "+f"(d[42]), "+f"(d[43]), "+f"(d[44]), "+f"(d[45]), "+f"(d[46]), "+f"(d[47]), "+f"(d[48]), "+f"(d[49]), "+f"(d[50]), "+f"(d[51]), "+f"(d[52]), "+f"(d[53]), "+f"(d[54]), "+f"(d[55]), "+f"(d[56]), "+f"(d[57]), "+f"(d[58]), "+f"(d[59]), "+f"(d[60]), "+f"(d[61]), "+f"(d[62]), "+f"(d[63]), "+f"(d[64]), "+f"(d[65]), "+f"(d[66]), "+f"(d[67]), "+f"(d[68]), "+f"(d[69]), "+f"(d[70]), "+f"(d[71]), "+f"(d[72]), "+f"(d[73]), "+f"(d[74]), "+f"(d[75]), "+f"(d[76]), "+f"(d[77]), "+f"(d[78]), "+f"(d[79]), "+f"(d[80]), "+f"(d[81]), "+f"(d[82]), "+f"(d[83]), "+f"(d[84]), "+f"(d[85]), "+f"(d[86]), "+f"(d[87]), "+f"(d[88]), "+f"(d[89]), "+f"(d[90]), "+f"(d[91]), "+f"(d[92]), "+f"(d[93]), "+f"(d[94]), "+f"(d[95]) : "l"(da), "l"(db), "r"(sd));
}
__device__ __forceinline__ void wgmma_ss_n128_tb(float* d, uint64_t da, uint64_t db, int sd) {
  asm volatile("{.reg .pred p; setp.ne.b32 p, %66, 0; wgmma.mma_async.sync.aligned.m64n128k16.f32.bf16.bf16 {%0,%1,%2,%3,%4,%5,%6,%7,%8,%9,%10,%11,%12,%13,%14,%15,%16,%17,%18,%19,%20,%21,%22,%23,%24,%25,%26,%27,%28,%29,%30,%31,%32,%33,%34,%35,%36,%37,%38,%39,%40,%41,%42,%43,%44,%45,%46,%47,%48,%49,%50,%51,%52,%53,%54,%55,%56,%57,%58,%59,%60,%61,%62,%63}, %64, %65, p, 1, 1, 0, 1;}"
    : "+f"(d[0]), "+f"(d[1]), "+f"(d[2]), "+f"(d[3]), "+f"(d[4]), "+f"(d[5]), "+f"(d[6]), "+f"(d[7]), "+f"(d[8]), "+f"(d[9]), "+f"(d[10]), "+f"(d[11]), "+f"(d[12]), "+f"(d[13]), "+f"(d[14]), "+f"(d[15]), "+f"(d[16]), "+f"(d[17]), "+f"(d[18]), "+f"(d[19]), "+f"(d[20]), "+f"(d[21]), "+f"(d[22]), "+f"(d[23]), "+f"(d[24]), "+f"(d[25]), "+f"(d[26]), "+f"(d[27]), "+f"(d[28]), "+f"(d[29]), "+f"(d[30]), "+f"(d[31]), "+f"(d[32]), "+f"(d[33]), "+f"(d[34]), "+f"(d[35]), "+f"(d[36]), "+f"(d[37]), "+f"(d[38]), "+f"(d[39]), "+f"(d[40]), "+f"(d[41]), "+f"(d[42]), "+f"(d[43]), "+f"(d[44]), "+f"(d[45]), "+f"(d[46]), "+f"(d[47]), "+f"(d[48]), "+f"(d[49]), "+f"(d[50]), "+f"(d[51]), "+f"(d[52]), "+f"(d[53]), "+f"(d[54]), "+f"(d[55]), "+f"(d[56]), "+f"(d[57]), "+f"(d[58]), "+f"(d[59]), "+f"(d[60]), "+f"(d[61]), "+f"(d[62]), "+f"(d[63]) : "l"(da), "l"(db), "r"(sd));
}
template<int SD> __device__ __forceinline__ void wgmma_rs_n64(float* d, const uint32_t* a, uint64_t db) {
  asm volatile("{.reg .pred p; setp.ne.b32 p, %37, 0; wgmma.mma_async.sync.aligned.m64n64k16.f32.bf16.bf16 {%0,%1,%2,%3,%4,%5,%6,%7,%8,%9,%10,%11,%12,%13,%14,%15,%16,%17,%18,%19,%20,%21,%22,%23,%24,%25,%26,%27,%28,%29,%30,%31}, {%32,%33,%34,%35}, %36, p, 1, 1, 0;}"
    : "+f"(d[0]), "+f"(d[1]), "+f"(d[2]), "+f"(d[3]), "+f"(d[4]), "+f"(d[5]), "+f"(d[6]), "+f"(d[7]), "+f"(d[8]), "+f"(d[9]), "+f"(d[10]), "+f"(d[11]), "+f"(d[12]), "+f"(d[13]), "+f"(d[14]), "+f"(d[15]), "+f"(d[16]), "+f"(d[17]), "+f"(d[18]), "+f"(d[19]), "+f"(d[20]), "+f"(d[21]), "+f"(d[22]), "+f"(d[23]), "+f"(d[24]), "+f"(d[25]), "+f"(d[26]), "+f"(d[27]), "+f"(d[28]), "+f"(d[29]), "+f"(d[30]), "+f"(d[31]) : "r"(a[0]), "r"(a[1]), "r"(a[2]), "r"(a[3]), "l"(db), "n"(SD));
}
template<int SD> __device__ __forceinline__ void wgmma_rs_n24(float* d, const uint32_t* a, uint64_t db) {
  asm volatile("{.reg .pred p; setp.ne.b32 p, %17, 0; wgmma.mma_async.sync.aligned.m64n24k16.f32.bf16.bf16 {%0,%1,%2,%3,%4,%5,%6,%7,%8,%9,%10,%11}, {%12,%13,%14,%15}, %16, p, 1, 1, 0;}"
    : "+f"(d[0]), "+f"(d[1]), "+f"(d[2]), "+f"(d[3]), "+f"(d[4]), "+f"(d[5]), "+f"(d[6]), "+f"(d[7]), "+f"(d[8]), "+f"(d[9]), "+f"(d[10]), "+f"(d[11]) : "r"(a[0]), "r"(a[1]), "r"(a[2]), "r"(a[3]), "l"(db), "n"(SD));
}
template<int SD> __device__ __forceinline__ void wgmma_rs_n32(float* d, const uint32_t* a, uint64_t db) {
  asm volatile("{.reg .pred p; setp.ne.b32 p, %21, 0; wgmma.mma_async.sync.aligned.m64n32k16.f32.bf16.bf16 {%0,%1,%2,%3,%4,%5,%6,%7,%8,%9,%10,%11,%12,%13,%14,%15}, {%16,%17,%18,%19}, %20, p, 1, 1, 0;}"
    : "+f"(d[0]), "+f"(d[1]), "+f"(d[2]), "+f"(d[3]), "+f"(d[4]), "+f"(d[5]), "+f"(d[6]), "+f"(d[7]), "+f"(d[8]), "+f"(d[9]), "+f"(d[10]), "+f"(d[11]), "+f"(d[12]), "+f"(d[13]), "+f"(d[14]), "+f"(d[15]) : "r"(a[0]), "r"(a[1]), "r"(a[2]), "r"(a[3]), "l"(db), "n"(SD));
}
template<int SD> __device__ __forceinline__ void wgmma_rs_n40(float* d, const uint32_t* a, uint64_t db) {
  asm volatile("{.reg .pred p; setp.ne.b32 p, %25, 0; wgmma.mma_async.sync.aligned.m64n40k16.f32.bf16.bf16 {%0,%1,%2,%3,%4,%5,%6,%7,%8,%9,%10,%11,%12,%13,%14,%15,%16,%17,%18,%19}, {%20,%21,%22,%23}, %24, p, 1, 1, 0;}"
    : "+f"(d[0]), "+f"(d[1]), "+f"(d[2]), "+f"(d[3]), "+f"(d[4]), "+f"(d[5]), "+f"(d[6]), "+f"(d[7]), "+f"(d[8]), "+f"(d[9]), "+f"(d[10]), "+f"(d[11]), "+f"(d[12]), "+f"(d[13]), "+f"(d[14]), "+f"(d[15]), "+f"(d[16]), "+f"(d[17]), "+f"(d[18]), "+f"(d[19]) : "r"(a[0]), "r"(a[1]), "r"(a[2]), "r"(a[3]), "l"(db), "n"(SD));
}
template<int SD> __device__ __forceinline__ void wgmma_rs_n24_tb(float* d, const uint32_t* a, uint64_t db) {
  asm volatile("{.reg .pred p; setp.ne.b32 p, %17, 0; wgmma.mma_async.sync.aligned.m64n24k16.f32.bf16.bf16 {%0,%1,%2,%3,%4,%5,%6,%7,%8,%9,%10,%11}, {%12,%13,%14,%15}, %16, p, 1, 1, 1;}"
    : "+f"(d[0]), "+f"(d[1]), "+f"(d[2]), "+f"(d[3]), "+f"(d[4]), "+f"(d[5]), "+f"(d[6]), "+f"(d[7]), "+f"(d[8]), "+f"(d[9]), "+f"(d[10]), "+f"(d[11]) : "r"(a[0]), "r"(a[1]), "r"(a[2]), "r"(a[3]), "l"(db), "n"(SD));
}

constexpr uint64_t DESC_SW128 = (uint64_t)1 << 62;
constexpr uint64_t DESC_SW32 = (uint64_t)3 << 62;
__device__ __forceinline__ uint64_t mk_desc(uint64_t sw, uint32_t addr, uint32_t lbo, uint32_t sbo) {
    return sw | ((uint64_t)(sbo >> 4) << 32) | ((uint64_t)(lbo >> 4) << 16) | (uint64_t)((addr & 0x3FFFF) >> 4);
}

constexpr uint32_t SM_BASE = 1024;
constexpr uint32_t P1_STAGE = 40960;
constexpr uint32_t P1_STGA = 98304;
constexpr uint32_t P1_RED = 147456;
constexpr uint32_t AT_Q = 0, AT_K = 16384, AT_V = 81920, AT_TAB = 163840, AT_ONES = 230400, AT_CT = 230912;
constexpr uint32_t P3_O = AT_TAB;
constexpr uint32_t BAR = 229376;
constexpr uint32_t B_FULL = BAR, B_EMPTY = BAR + 32;
constexpr uint32_t B_KV = BAR + 96, B_Q = BAR + 160, B_CONS = BAR + 168, B_WFULL = BAR + 232, B_OFULL = BAR + 296, B_OEMPTY = BAR + 328;
constexpr uint32_t B_STFREE = BAR + 360;
constexpr uint32_t OFF_MAX = BAR + 416, OFF_NORM = BAR + 512;
constexpr int SMEM_BYTES = BAR + 1024 + 832;
constexpr uint32_t B_TAB = BAR + 64;
constexpr float QSCALE = 0.25f * 1.4426950408889634f;

struct Maps { CUtensorMap xA, xB, wA, wB, o, o16, woA, woB, out; };

__device__ __forceinline__ void phase_qkv(uint8_t* smem, const Maps& mp) {
    constexpr uint32_t sb = SM_BASE;
    const int tid = threadIdx.x, warp = tid >> 5, lane = tid & 31;
    const int nt = blockIdx.x & 7, mt = blockIdx.x >> 3;
    float* sMax = (float*)(smem + OFF_MAX);
    auto produce = [&](int kb) {
        const int s = kb & 3;
        const uint32_t full = sb + B_FULL + 8 * s, st = sb + s * P1_STAGE;
        mbar_expect_tx(full, P1_STAGE);
        tma_load_2d(st, kb < 8 ? &mp.xB : &mp.xA, (kb & 7) * 64, mt * 128, full);
#pragma unroll
        for (int j = 0; j < 3; j++) tma_load_2d(st + 16384 + j * 8192, kb < 8 ? &mp.wB : &mp.wA, j * 512 + nt * 64, (kb & 7) * 64, full);
    };
    if (tid == 0) {
        tma_prefetch_desc(&mp.xB); tma_prefetch_desc(&mp.wB);
        for (int i = 0; i < 4; i++) { mbar_init(sb + B_FULL + 8 * i, 1); mbar_init(sb + B_EMPTY + 8 * i, 2); }
        fence_mbar_init();
        for (int kb = 0; kb < 4; kb++) produce(kb);
        tma_prefetch_desc(&mp.xA); tma_prefetch_desc(&mp.wA);
    }
    if (tid == 32) {
        for (int i = 0; i < 4; i++) mbar_init(sb + B_STFREE + 8 * i, 2);
        mbar_init(sb + B_Q, 1); mbar_init(sb + B_TAB, 256);
        for (int i = 0; i < 8; i++) { mbar_init(sb + B_KV + 8 * i, 1); mbar_init(sb + B_CONS + 8 * i, 4); mbar_init(sb + B_WFULL + 8 * i, 1); }
        for (int i = 0; i < 4; i++) { mbar_init(sb + B_OFULL + 8 * i, 1); mbar_init(sb + B_OEMPTY + 8 * i, 2); }
        fence_mbar_init();
    }
    if (tid >= 64 && tid < 72) sMax[tid - 64] = 0.f;
    __syncthreads();

    const int wg = __shfl_sync(0xffffffffu, warp >> 2, 0);
    const int branchB = wg < 2;
    const int wh = wg & 1;
    const int kb0 = branchB ? 0 : 8;
    float acc[96];
#pragma unroll
    for (int i = 0; i < 96; i++) acc[i] = 0.f;
    fence_regs(acc);
    if (!branchB) {
        const int w = warp & 7, j = w * 32 + lane;
        const float f = (j + 0.5f) * (1.f / 256.f);
        const uint32_t val = (uint32_t)(__float2int_rn((exp2f(f) - 1.f) * 128.f) - (j >> 1) + (63 << 7) - 0x8000);
        uint4* tb = (uint4*)(smem + AT_TAB) + w * 32 * 8 + lane;
#pragma unroll
        for (int i = 0; i < 8; i++) {
            const uint32_t v = __shfl_sync(0xffffffffu, val, i * 4 + (lane >> 3));
            tb[i * 32] = make_uint4(v, v, v, v);
            tb[2048 + i * 32] = make_uint4(v << 16, v << 16, v << 16, v << 16);
        }
        if (w == 0) { for (int i = lane; i < 128; i += 32) ((uint32_t*)(smem + AT_ONES))[i] = 0x3F803F80u; }
        if (w == 1) {
            for (int i = lane; i < 64; i += 32) {
                const int r = i >> 3, ww = i & 7, chunk = (ww >> 2) ^ (r >> 2);
                ((uint32_t*)(smem + AT_CT))[i] = (chunk == 0 && (ww & 3) == 0) ? 0x000043A0u : 0u;
            }
        }
        if (w == 2 && lane < 8) ((uint32_t*)(smem + AT_CT + 256))[lane] = lane < 2 ? 0x00003F80u : 0u;
        fence_async_smem();
        mbar_arrive(sb + B_TAB);
        named_bar(3, 512);
    }
    const uint64_t dA0 = mk_desc(DESC_SW128, sb + wh * 8192, 16, 1024);
#pragma unroll
    for (int i = 0; i < 8; i++) {
        const int kb = kb0 + i, s = i & 3;
        mbar_wait(sb + B_FULL + 8 * s, (i >> 2) & 1);
        const uint64_t dA = dA0 + (uint64_t)(s * (P1_STAGE >> 4)), dB = mk_desc(DESC_SW128, sb + s * P1_STAGE + 16384, 8192, 1024);
        wg_fence();
#pragma unroll
        for (int k = 0; k < 4; k++) wgmma_ss_n192_tb(acc, dA + k * 2, dB + k * 128, 1);
        wg_commit();
        if (i == 7 && branchB) asm volatile("bar.arrive 3, 512;" ::: "memory");
        if (i > 0) {
            wg_wait<1>();
            if (i >= 5 && !branchB && (tid & 127) == 0) mbar_arrive(sb + B_STFREE + 8 * (i - 5));
            if (kb + 3 < 16) {
                const uint32_t eb = sb + B_EMPTY + 8 * ((i - 1) & 3);
                if ((tid & 127) == 0) {
                    mbar_arrive(eb);
                    if (wh == 0) { mbar_wait(eb, ((i - 1) >> 2) & 1); produce(kb + 3); }
                }
                __syncwarp();
            }
        }
    }
    wg_wait<0>();
    fence_regs(acc);

    const int wq = warp & 3, g = lane >> 2, t = lane & 3;
    const int lr = (lane & 7) + ((lane >> 3) & 1) * 8;
    const int lc = lane >> 4;
    const int row0 = mt * 128;
    const int w8 = warp & 7;
    if (branchB) {
        {
            const uint32_t eb = sb + B_EMPTY + 8 * 3;
            if ((tid & 127) == 0) {
                mbar_arrive(eb);
                if (wh == 0) { mbar_wait(eb, 1); produce(11); }
            }
            __syncwarp();
        }
        const int orow = g + (t >> 1) * 8;
        const uint32_t ooff = (uint32_t)(row0 + wh * 64 + wq * 16 + orow) * 32 + (((t & 1) ^ ((orow & 7) >> 2)) << 4);
        const bool o1 = t & 1, o2 = t & 2;
        uint32_t mymax = 0;
#pragma unroll
        for (int sl = 0; sl < 12; sl++) {
            float* a = acc + sl * 8;
            if (sl < 4) {
#pragma unroll
                for (int i = 0; i < 8; i++) a[i] *= QSCALE;
            }
            if (sl < 8) {
                const float n0 = fmaf(a[0], a[0], fmaf(a[1], a[1], fmaf(a[4], a[4], a[5] * a[5])));
                const float n1 = fmaf(a[2], a[2], fmaf(a[3], a[3], fmaf(a[6], a[6], a[7] * a[7])));
                const uint32_t m = __reduce_max_sync(0xffffffffu, __float_as_uint(fmaxf(n0, n1)));
                if (lane == sl) mymax = m;
            }
            const uint32_t w0 = pack_bf16(a[0], a[1]), w2 = pack_bf16(a[2], a[3]), w1 = pack_bf16(a[4], a[5]), w3 = pack_bf16(a[6], a[7]);
            const uint32_t r0 = __shfl_xor_sync(0xffffffffu, o1 ? w0 : w1, 1), r1 = __shfl_xor_sync(0xffffffffu, o1 ? w2 : w3, 1);
            const uint32_t x0 = o1 ? r0 : w0, x1 = o1 ? w1 : r0, y0 = o1 ? r1 : w2, y1 = o1 ? w3 : r1;
            const uint32_t q0 = __shfl_xor_sync(0xffffffffu, o2 ? x0 : y0, 2), q1 = __shfl_xor_sync(0xffffffffu, o2 ? x1 : y1, 2);
            uint4 val;
            val.x = o2 ? q0 : x0; val.y = o2 ? q1 : x1; val.z = o2 ? y0 : q0; val.w = o2 ? y1 : q1;
            const int ty = sl >> 2, head = nt * 4 + (sl & 3);
            uint8_t* dst = (uint8_t*)((ty == 0 ? g_qB : (ty == 1 ? g_kB : g_vB)) + (size_t)head * S_LEN * 16);
            *(uint4*)(dst + ooff) = val;
        }
        if (lane < 8) atomicMax((unsigned int*)&sMax[lane], mymax);
        named_bar(1, 256);
        if (w8 == 7 && lane >= 8 && lane < 16) { const int i = lane - 8; (i < 4 ? g_qn : g_kn)[(nt * 4 + (i & 3)) * 16 + mt] = sMax[i]; }
        named_bar(1, 256);
        const int h = blockIdx.x >> 2, qb = blockIdx.x & 3;
        if (tid == 0) signal_add(&g_cnt.qkvB[nt]);
        auto ld_k = [&](int c) {
            mbar_expect_tx(sb + B_KV + 8 * c, 16384);
            bulk_g2s(sb + AT_K + c * 8192, g_kB + ((size_t)h * S_LEN + c * 256) * 16, 8192, sb + B_KV + 8 * c);
        };
        auto ld_v = [&](int c) { bulk_g2s(sb + AT_V + c * 8192, g_vB + ((size_t)h * S_LEN + c * 256) * 16, 8192, sb + B_KV + 8 * c); };
        if (tid == 32) {
            spin_ge(&g_cnt.qkvB[h >> 2], 16);
            fence_async_all();
            mbar_wait(sb + B_STFREE, 0);
            mbar_expect_tx(sb + B_Q, 16384 + 128);
            bulk_g2s(sb + AT_Q, g_qB + ((size_t)h * S_LEN + qb * 512) * 16, 16384, sb + B_Q);
            ld_k(0);
            bulk_g2s(sb + OFF_NORM, g_qn + h * 16, 64, sb + B_Q);
            bulk_g2s(sb + OFF_NORM + 64, g_kn + h * 16, 64, sb + B_Q);
            mbar_wait(sb + B_STFREE + 16, 0);
            ld_v(0); ld_k(1); ld_v(1);
        }
        __syncwarp();
    } else {
        if ((tid & 127) == 0) mbar_arrive(sb + B_STFREE + 8 * 3);
        named_bar(2, 256);
        const uint32_t stg = sb + P1_STGA;
        const uint32_t stAddr = stg + (wh * 64 + wq * 16 + lr) * 32 + (((lc ^ ((lr & 7) >> 2))) << 4);
#pragma unroll
        for (int sl = 0; sl < 12; sl++) {
            float* a = acc + sl * 8;
            uint32_t p0 = pack_bf16(a[0], a[1]), p1 = pack_bf16(a[2], a[3]), p2 = pack_bf16(a[4], a[5]), p3 = pack_bf16(a[6], a[7]);
            if (sl >= 4 && sl < 8) { p0 = phi_bf16x2(p0); p1 = phi_bf16x2(p1); p2 = phi_bf16x2(p2); p3 = phi_bf16x2(p3); }
            stsm_x4(stAddr + sl * 4096, p0, p1, p2, p3);
        }
        named_bar(2, 256);
#pragma unroll
        for (int sl = 0; sl < 4; sl++)
            *(uint4*)((uint8_t*)(g_qA + ((size_t)(nt * 4 + sl) * S_LEN + row0) * 16) + (tid - 256) * 16) = *(const uint4*)(smem + P1_STGA + sl * 4096 + (tid - 256) * 16);
        const int hh = w8 & 3;
        const uint32_t pkb = stg + (4 + hh) * 4096 + wh * 2048, vb = stg + (8 + hh) * 4096 + wh * 2048;
        float kv0[4] = {0.f, 0.f, 0.f, 0.f}, kv1[4] = {0.f, 0.f, 0.f, 0.f}, zz[4] = {0.f, 0.f, 0.f, 0.f};
        const int ar = (lane & 7) + (lane >> 4) * 8, ac = (lane >> 3) & 1;
        const int br = (lane & 7) + ((lane >> 3) & 1) * 8, bc = lane >> 4;
#pragma unroll
        for (int ks = 0; ks < 4; ks++) {
            uint32_t af[4], bf[4];
            ldsm_x4_t(pkb + (ks * 16 + ar) * 32 + ((ac ^ ((ar & 7) >> 2)) << 4), af);
            ldsm_x4_t(vb + (ks * 16 + br) * 32 + ((bc ^ ((br & 7) >> 2)) << 4), bf);
            mma_bf16(kv0, af, bf[0], bf[1]);
            mma_bf16(kv1, af, bf[2], bf[3]);
            mma_bf16(zz, af, 0x3F803F80u, 0x3F803F80u);
        }
        float* rp = (float*)(smem + P1_RED) + hh * 272;
        if (wh == 1) {
            rp[g * 16 + 2 * t] = kv0[0]; rp[g * 16 + 2 * t + 1] = kv0[1];
            rp[(g + 8) * 16 + 2 * t] = kv0[2]; rp[(g + 8) * 16 + 2 * t + 1] = kv0[3];
            rp[g * 16 + 8 + 2 * t] = kv1[0]; rp[g * 16 + 8 + 2 * t + 1] = kv1[1];
            rp[(g + 8) * 16 + 8 + 2 * t] = kv1[2]; rp[(g + 8) * 16 + 8 + 2 * t + 1] = kv1[3];
            if (t == 0) { rp[256 + g] = zz[0]; rp[256 + g + 8] = zz[2]; }
        }
        named_bar(2, 256);
        if (wh == 0) {
            float* gp = g_kvp + (size_t)(mt * NH + nt * 4 + hh) * 272;
            *(float2*)(gp + g * 16 + 2 * t) = make_float2(kv0[0] + rp[g * 16 + 2 * t], kv0[1] + rp[g * 16 + 2 * t + 1]);
            *(float2*)(gp + (g + 8) * 16 + 2 * t) = make_float2(kv0[2] + rp[(g + 8) * 16 + 2 * t], kv0[3] + rp[(g + 8) * 16 + 2 * t + 1]);
            *(float2*)(gp + g * 16 + 8 + 2 * t) = make_float2(kv1[0] + rp[g * 16 + 8 + 2 * t], kv1[1] + rp[g * 16 + 8 + 2 * t + 1]);
            *(float2*)(gp + (g + 8) * 16 + 8 + 2 * t) = make_float2(kv1[2] + rp[(g + 8) * 16 + 8 + 2 * t], kv1[3] + rp[(g + 8) * 16 + 8 + 2 * t + 1]);
            if (t == 0) { gp[256 + g] = zz[0] + rp[256 + g]; gp[256 + g + 8] = zz[2] + rp[256 + g + 8]; }
        }
    }
}

constexpr int AT_NT = 64;
constexpr int AT_NP = 32, AT_NP2 = 40;
constexpr float AT_SAFE2 = 56.f * 56.f;

__device__ __forceinline__ uint32_t ex2_tab2(float ya, float yb, uint32_t lane4) {
    const uint32_t a = __float_as_uint(ya), b = __float_as_uint(yb);
    uint32_t aa, ab, ta, tb, L;
    asm("lop3.b32 %0, %1, 0x7F80, %2, 0xEA;" : "=r"(aa) : "r"(a), "r"(lane4));
    asm("lop3.b32 %0, %1, 0x7F80, %2, 0xEA;" : "=r"(ab) : "r"(b), "r"(lane4));
    asm volatile("ld.shared.u32 %0, [%1+%2];" : "=r"(ta) : "r"(aa), "n"(SM_BASE + AT_TAB));
    asm volatile("ld.shared.u32 %0, [%1+%2];" : "=r"(tb) : "r"(ab), "n"(SM_BASE + AT_TAB + 32768));
    asm("prmt.b32 %0, %1, %2, 0x6521;" : "=r"(L) : "r"(a), "r"(b));
    return L + ta + tb;
}
template <int NT, int NP>
__device__ __forceinline__ void att_exp(const float* s, uint32_t* p, uint32_t lane4) {
    constexpr int PP = NP / 4, TOT = NT / 4;
#pragma unroll
    for (int i = 0; i < TOT; i++) {
        const int nb = (i * PP) / TOT, na = ((i + 1) * PP) / TOT;
        if (na != nb) p[nb] = ex2_tab2(s[2 * nb], s[2 * nb + 1], lane4);
        else { const int im = PP + i - nb; p[im] = pack_bf16(ex2f(s[2 * im]), ex2f(s[2 * im + 1])); }
    }
}

__device__ __forceinline__ void mbar_arrive_elect(uint32_t bar) {
    asm volatile("{.reg .pred p;\nelect.sync _|p, 0xffffffff;\n@p mbarrier.arrive.shared::cta.b64 _, [%0];\n}" ::"r"(bar) : "memory");
}
__device__ __forceinline__ void load_wo_elect(const Maps& mp, int branchB, int nt, int c) {
    constexpr uint32_t sb = SM_BASE;
    const CUtensorMap* tm = branchB ? &mp.woB : &mp.woA;
    asm volatile(
        "{.reg .pred p;\n"
        "elect.sync _|p, 0xffffffff;\n"
        "@p mbarrier.arrive.expect_tx.shared::cta.b64 _, [%0], 16384;\n"
        "@p cp.async.bulk.tensor.2d.shared::cluster.global.mbarrier::complete_tx::bytes [%1], [%3, {%4, %6}], [%0];\n"
        "@p cp.async.bulk.tensor.2d.shared::cluster.global.mbarrier::complete_tx::bytes [%2], [%3, {%5, %6}], [%0];\n"
        "}" ::"r"(sb + B_WFULL + 8 * c), "r"(sb + AT_K + c * 8192), "r"(sb + AT_V + c * 8192), "l"(tm), "r"(nt * 128), "r"(nt * 128 + 64), "r"(c * 64)
        : "memory");
}
__device__ __forceinline__ void load_kv_elect(int h, int c) {
    constexpr uint32_t sb = SM_BASE;
    asm volatile(
        "{.reg .pred p;\n"
        "elect.sync _|p, 0xffffffff;\n"
        "@p mbarrier.arrive.expect_tx.shared::cta.b64 _, [%0], 16384;\n"
        "@p cp.async.bulk.shared::cluster.global.mbarrier::complete_tx::bytes [%1], [%3], 8192, [%0];\n"
        "@p cp.async.bulk.shared::cluster.global.mbarrier::complete_tx::bytes [%2], [%4], 8192, [%0];\n"
        "}" ::"r"(sb + B_KV + 8 * c), "r"(sb + AT_K + c * 8192), "r"(sb + AT_V + c * 8192),
        "l"(g_kB + ((size_t)h * S_LEN + c * 256) * 16), "l"(g_vB + ((size_t)h * S_LEN + c * 256) * 16) : "memory");
}
__device__ __forceinline__ void load_wo(const Maps& mp, int branchB, int nt, int c) {
    constexpr uint32_t sb = SM_BASE;
    const CUtensorMap* tm = branchB ? &mp.woB : &mp.woA;
    mbar_expect_tx(sb + B_WFULL + 8 * c, 16384);
    tma_load_2d(sb + AT_K + c * 8192, tm, nt * 128, c * 64, sb + B_WFULL + 8 * c);
    tma_load_2d(sb + AT_V + c * 8192, tm, nt * 128 + 64, c * 64, sb + B_WFULL + 8 * c);
}

__device__ __forceinline__ void phase_attn(uint8_t* smem, const Maps& mp) {
    constexpr uint32_t sb = SM_BASE;
    const int tid = threadIdx.x, warp = (tid >> 5) & 3, lane = tid & 31;
    const int wg = __shfl_sync(0xffffffffu, tid >> 7, 0);
    const int wwarp = __shfl_sync(0xffffffffu, warp, 0);
    const int h = blockIdx.x >> 2, qb = blockIdx.x & 3;
    constexpr int NCH = 8;
    constexpr uint32_t sK = sb + AT_K, sV = sb + AT_V, sQ = sb + AT_Q, sBar = sb + B_KV;

    named_bar(4 + wg, 128);
    mbar_wait(sb + B_TAB, 0);
    mbar_wait(sb + B_Q, 0);
    if (wg >= 2) {
        named_bar(2, 256);
        if (wwarp < 3) load_kv_elect(h, 2 + (wg - 2) * 3 + wwarp);
    }
    __syncwarp();
    bool safe;
    {
        const float* nrm = (const float*)(smem + OFF_NORM);
        const float qv = lane < 4 ? nrm[qb * 4 + lane] : 0.f;
        const float kv = lane < 16 ? nrm[16 + lane] : 0.f;
        const uint32_t qm = __reduce_max_sync(0xffffffffu, __float_as_uint(qv));
        const uint32_t km = __reduce_max_sync(0xffffffffu, __float_as_uint(kv));
        safe = (__uint_as_float(qm) * __uint_as_float(km) * (16.f * 1.05f) < AT_SAFE2);
    }
    const uint64_t dK0 = mk_desc(DESC_SW32, sK, 16, 256);
    const uint64_t dC = mk_desc(DESC_SW32, sb + AT_CT, 16, 0);
    const uint64_t dV0 = mk_desc(DESC_SW32, sV, AT_ONES - AT_V, 256);
    constexpr int64_t VSTEP = 32 - (32 << 16);
    const uint32_t lane4 = lane * 4;
    uint32_t aone[4];
    asm volatile("ld.shared.v4.u32 {%0,%1,%2,%3}, [%4];" : "=r"(aone[0]), "=r"(aone[1]), "=r"(aone[2]), "=r"(aone[3]) : "r"(sb + AT_CT + 256 + ((lane & 3) == 0 ? 0 : 16)));
    const int g = lane >> 2, t = lane & 3;
    constexpr int NT = AT_NT, NP = AT_NP;
    const int oBranch = blockIdx.x >> 6, oNt = blockIdx.x & 3;

#pragma unroll 1
    for (int qi = 0; qi < 2; qi++) {
        const int qt = wg * 2 + qi;
        const int row0 = qb * 512 + qt * 64 + warp * 16;
        uint32_t qa[4];
        ldsm_x4(sQ + (qt * 64 + warp * 16 + (lane & 7) + ((lane >> 3) & 1) * 8) * 32 + ((((lane >> 4) ^ ((lane & 7) >> 2))) << 4), qa);
        float o[12], s[NT / 2];
#pragma unroll
        for (int i = 0; i < 12; i++) o[i] = 0.f;
#pragma unroll
        for (int i = 0; i < NT / 2; i++) s[i] = 0.f;
        fence_regs(o); fence_regs(s);
        if (safe) {
            uint32_t pa[NT / 4], pb[NT / 4];
            auto issue_qk = [&](uint64_t dK, int np) {
                wgmma_rs_n64<0>(s, qa, dK);
                if (np == 24) wgmma_rs_n24<1>(s, aone, dC); else if (np == 32) wgmma_rs_n32<1>(s, aone, dC); else wgmma_rs_n40<1>(s, aone, dC);
            };
            mbar_wait(sBar, 0);
            wg_fence();
            issue_qk(dK0, NP);
            wg_commit();
            wg_wait<0>();
            fence_regs(s);
            att_exp<NT, NP>(s, pa, lane4);
            if (qi == 0 && wg == 2 && wwarp == 0) {
                asm volatile("{.reg .pred p;\nelect.sync _|p, 0xffffffff;\n@p red.release.gpu.global.add.s32 [%0], 1;\n}" ::"l"(&g_cnt.qkvA[blockIdx.x & 7]) : "memory");
            }
            uint64_t dK = dK0, dV = dV0;
            auto step = [&](uint32_t (&pc)[NT / 4], uint32_t (&pn)[NT / 4], bool last, int jt) {
                wg_fence();
                if (!last) { issue_qk(dK + (uint64_t)(jt * NT * 2 + NT * 2), (jt & 1) ? NP : AT_NP2); wg_commit(); }
#pragma unroll
                for (int kk = 0; kk < NT / 16; kk++) wgmma_rs_n24_tb<1>(o, pc + kk * 4, dV + (uint64_t)((int64_t)(jt * (NT / 16) + kk) * VSTEP));
                wg_commit();
                if (!last) {
                    wg_wait<1>();
                    fence_regs(s);
                    if (jt & 1) att_exp<NT, NP>(s, pn, lane4); else att_exp<NT, AT_NP2>(s, pn, lane4);
                }
                if (last || jt == 3) { wg_wait<0>(); fence_regs(pc); fence_regs(o); }
            };
            constexpr int TPC = 256 / NT;
#pragma unroll 1
            for (int cch = 0; cch < NCH; cch++) {
#pragma unroll
                for (int jj = 0; jj < TPC; jj += 2) {
                    step(pa, pb, false, jj);
                    if (jj + 2 == TPC) {
                        if (cch == NCH - 1) break;
                        mbar_wait(sBar + 8 * (cch + 1), 0);
                    }
                    step(pb, pa, false, jj + 1);
                }
                dK += 256 * 2; dV += (uint64_t)(16 * VSTEP);
                if (qi == 1 && wwarp == 0 && cch < NCH - 1) {
                    mbar_arrive_elect(sb + B_CONS + 8 * cch);
                    if (cch >= 1 && wg == ((cch - 1) & 3)) { mbar_wait(sb + B_CONS + 8 * (cch - 1), 0); load_wo_elect(mp, oBranch, oNt, cch - 1); }
                }
            }
            dV -= (uint64_t)(16 * VSTEP);
            step(pb, pa, true, TPC - 1);
            if (qi == 1 && wwarp == 0) {
                mbar_arrive_elect(sb + B_CONS + 8 * 7);
                if (wg == 2) { mbar_wait(sb + B_CONS + 8 * 6, 0); load_wo_elect(mp, oBranch, oNt, 6); }
                if (wg == 3) { mbar_wait(sb + B_CONS + 8 * 7, 0); load_wo_elect(mp, oBranch, oNt, 7); }
            }
        } else {
            if (qi == 0 && tid == 256) signal_add(&g_cnt.qkvA[blockIdx.x & 7]);
            float m0 = -INFINITY, m1 = -INFINITY;
            uint32_t p[NT / 4];
#pragma unroll 1
            for (int j = 0; j < S_LEN / NT; j++) {
                if ((j * NT) % 256 == 0) mbar_wait(sBar + 8 * ((j * NT) / 256), 0);
                wg_fence();
                wgmma_rs_n64<0>(s, qa, dK0 + (uint64_t)(j * NT * 2));
                wg_commit();
                wg_wait<0>();
                fence_regs(s); fence_regs(o);
                float t0 = m0, t1 = m1;
#pragma unroll
                for (int i = 0; i < NT / 2; i += 4) { t0 = fmaxf(t0, fmaxf(s[i], s[i + 1])); t1 = fmaxf(t1, fmaxf(s[i + 2], s[i + 3])); }
                t0 = fmaxf(t0, __shfl_xor_sync(0xffffffffu, t0, 1)); t0 = fmaxf(t0, __shfl_xor_sync(0xffffffffu, t0, 2));
                t1 = fmaxf(t1, __shfl_xor_sync(0xffffffffu, t1, 1)); t1 = fmaxf(t1, __shfl_xor_sync(0xffffffffu, t1, 2));
                const float r0 = ex2f(m0 - t0), r1 = ex2f(m1 - t1);
                m0 = t0; m1 = t1;
#pragma unroll
                for (int i = 0; i < 12; i += 4) { o[i] *= r0; o[i + 1] *= r0; o[i + 2] *= r1; o[i + 3] *= r1; }
#pragma unroll
                for (int i = 0; i < NT / 4; i += 2) {
                    p[i] = pack_bf16(ex2f(s[2 * i] - m0), ex2f(s[2 * i + 1] - m0));
                    p[i + 1] = pack_bf16(ex2f(s[2 * i + 2] - m1), ex2f(s[2 * i + 3] - m1));
                }
                fence_regs(o);
                wg_fence();
#pragma unroll
                for (int kk = 0; kk < NT / 16; kk++) wgmma_rs_n24_tb<1>(o, p + kk * 4, dV0 + (uint64_t)((int64_t)(j * (NT / 16) + kk) * VSTEP));
                wg_commit();
                wg_wait<0>();
                fence_regs(p);
            }
            fence_regs(o);
        }
        const float l0 = 1.f / o[8], l1 = 1.f / o[10];
        uint32_t* op0 = (uint32_t*)(g_o + (size_t)(row0 + g) * 1024 + 512 + h * 16);
        uint32_t* op1 = (uint32_t*)(g_o + (size_t)(row0 + g + 8) * 1024 + 512 + h * 16);
        op0[t] = pack_bf16(o[0] * l0, o[1] * l0);
        op0[4 + t] = pack_bf16(o[4] * l0, o[5] * l0);
        op1[t] = pack_bf16(o[2] * l1, o[3] * l1);
        op1[4 + t] = pack_bf16(o[6] * l1, o[7] * l1);
    }
    named_bar(4 + wg, 128);
    if ((tid & 127) == 0) signal_add(&g_cnt.oB[(qb * 4 + wg) * 8 + (h >> 2)]);
    __syncthreads();
    if (!safe && tid == 0) {
        for (int c = 0; c < 8; c++) load_wo(mp, oBranch, oNt, c);
    }
}

__device__ __forceinline__ void phase_out(uint8_t* smem, const Maps& mp) {
    (void)smem;
    constexpr uint32_t sb = SM_BASE;
    const int tid = threadIdx.x, warp = tid >> 5, lane = tid & 31;
    const int branchB = blockIdx.x >> 6;
    const int mt = (blockIdx.x & 63) >> 2, nt = blockIdx.x & 3;
    const int wg = __shfl_sync(0xffffffffu, warp >> 2, 0);
    if (wg == 2) {
        if (tid < 256 + 32) {
            if (lane == 0) { tma_prefetch_desc(&mp.o); tma_prefetch_desc(&mp.out); }
            const int* cnt = branchB ? &g_cnt.oB[mt * 8 + (lane & 7)] : &g_cnt.oA;
            int next = 0, spins = 0;
            while (next < 8) {
                int v;
                asm volatile("ld.acquire.gpu.global.s32 %0, [%1];" : "=r"(v) : "l"(cnt) : "memory");
                const uint32_t ready = __ballot_sync(0xffffffffu, v >= 4);
                __syncwarp();
                if (lane == 0) {
                    fence_async_all();
                    for (int kb = next; kb < 8 && ((ready >> kb) & 1); kb++) {
                        const int s = kb & 3;
                        if (kb >= 4) mbar_wait(sb + B_OEMPTY + 8 * s, 0);
                        mbar_expect_tx(sb + B_OFULL + 8 * s, 16384);
                        tma_load_2d(sb + P3_O + s * 16384, &mp.o, branchB * 512 + kb * 64, mt * 128, sb + B_OFULL + 8 * s);
                    }
                }
                while (next < 8 && ((ready >> next) & 1)) next++;
                __syncwarp();
                if (++spins > (1 << 22)) __trap();
                if (next < 8) __nanosleep(SPIN_NS);
            }
            if (lane == 0) finish_ticket();
        }
        return;
    }
    if (wg == 3) return;
    float acc[64];
#pragma unroll
    for (int i = 0; i < 64; i++) acc[i] = 0.f;
    fence_regs(acc);
    const uint64_t dA0 = mk_desc(DESC_SW128, sb + P3_O + wg * 8192, 16, 1024);
#pragma unroll
    for (int kb = 0; kb < 8; kb++) {
        const int s = kb & 3;
        mbar_wait(sb + B_WFULL + 8 * kb, 0);
        mbar_wait(sb + B_OFULL + 8 * s, kb >> 2);
        const uint64_t dA = dA0 + (uint64_t)(s * (16384 >> 4));
        const uint64_t dB = mk_desc(DESC_SW128, sb + AT_K + kb * 8192, AT_V - AT_K, 1024);
        wg_fence();
#pragma unroll
        for (int k = 0; k < 4; k++) wgmma_ss_n128_tb(acc, dA + k * 2, dB + k * 128, 1);
        wg_commit();
        if (kb >= 1 && kb <= 4) {
            wg_wait<1>();
            if ((tid & 127) == 0) mbar_arrive(sb + B_OEMPTY + 8 * (kb - 1));
        }
    }
    wg_wait<0>();
    fence_regs(acc);
    const int wq = warp & 3;
    const uint32_t stg = sb + P3_O + wg * 8192;
    const int lr = wq * 16 + (lane & 7) + ((lane >> 3) & 1) * 8, lc = lane >> 4;
#pragma unroll
    for (int j = 0; j < 8; j++) {
        const float* a = acc + j * 8;
        const int chunk = (j & 3) * 2 + lc;
        stsm_x4(stg + (j >> 2) * 16384 + lr * 128 + ((chunk ^ (lr & 7)) << 4),
                pack_bf16(a[0], a[1]), pack_bf16(a[2], a[3]), pack_bf16(a[4], a[5]), pack_bf16(a[6], a[7]));
    }
    fence_async_smem();
    named_bar(4 + wg, 128);
    if ((tid & 127) < 2) {
        const int j = tid & 1;
        tma_store_2d(&mp.out, stg + j * 16384, branchB * 512 + nt * 128 + j * 64, mt * 128 + wg * 64);
        bulk_commit();
        asm volatile("cp.async.bulk.wait_group.read 0;" ::: "memory");
    }
}

__device__ __noinline__ void linattn_mid(uint8_t* smem, int cta, const CUtensorMap* tmO16) {
    constexpr uint32_t sb = SM_BASE;
    const int tid = threadIdx.x, warp = tid >> 5, lane = tid & 31;
    constexpr int NBUF = 4;
    const uint32_t sBar = sb;
    const uint32_t sQ0 = sb + 1024;
    const uint32_t sSt = sQ0 + NBUF * 32768;
    float* skv = (float*)(smem + 1024 + NBUF * 32768 + 65536);
    if (tid == 0) { for (int i = 0; i < NBUF; i++) { mbar_init(sBar + 8 * i, 1); mbar_init(sBar + 64 + 8 * i, 16); } fence_mbar_init(); }
    __syncthreads();
    if (warp == 0 && lane == 0) { spin_ge(&g_cnt.qkvA[2 * cta], 16); spin_ge(&g_cnt.qkvA[2 * cta + 1], 16); }
    __syncthreads();
    if (lane == 0) fence_async_all();
    __syncwarp();
    auto load_chunk = [&](int c, int j) {
        bulk_g2s(sQ0 + (c % NBUF) * 32768 + j * 8192, g_qA + ((size_t)(cta * 8 + (c >> 3) * 4 + j) * S_LEN + (c & 7) * 256) * 16, 8192, sBar + 8 * (c % NBUF));
    };
    if (lane == 0 && warp < NBUF) {
        mbar_expect_tx(sBar + 8 * warp, 32768);
        for (int j = 0; j < 4; j++) load_chunk(warp, j);
    }
    {
        const int hh = tid >> 6, e = tid & 63;
        const float* gp = g_kvp + (size_t)(cta * 8 + hh) * 272 + e * 4;
        const float* gz = g_kvp + (size_t)(cta * 8 + ((tid >> 4) & 7)) * 272 + 256 + (tid & 15);
        float4 v0, v1, v2, v3, v4, v5, v6, v7;
        float z[16];
#define LD4(m) (*(const float4*)(gp + (size_t)(m) * NH * 272))
#define ADD4(a, b) (a).x += (b).x, (a).y += (b).y, (a).z += (b).z, (a).w += (b).w
        if (tid < 128) {
#pragma unroll
            for (int m = 0; m < 16; m++) z[m] = gz[(size_t)m * NH * 272];
        }
        v0 = LD4(0); v1 = LD4(1); v2 = LD4(2); v3 = LD4(3); v4 = LD4(4); v5 = LD4(5); v6 = LD4(6); v7 = LD4(7);
        {
            const float4 w0 = LD4(8), w1 = LD4(9), w2 = LD4(10), w3 = LD4(11), w4 = LD4(12), w5 = LD4(13), w6 = LD4(14), w7 = LD4(15);
            ADD4(v0, w0); ADD4(v1, w1); ADD4(v2, w2); ADD4(v3, w3); ADD4(v4, w4); ADD4(v5, w5); ADD4(v6, w6); ADD4(v7, w7);
        }
        ADD4(v0, v4); ADD4(v1, v5); ADD4(v2, v6); ADD4(v3, v7); ADD4(v0, v2); ADD4(v1, v3); ADD4(v0, v1);
#undef LD4
#undef ADD4
        *(float4*)(skv + hh * 272 + e * 4) = v0;
        if (tid < 128) {
#pragma unroll
            for (int w = 8; w > 0; w >>= 1) {
#pragma unroll
                for (int m = 0; m < w; m++) z[m] += z[m + w];
            }
            skv[((tid >> 4) & 7) * 272 + 256 + (tid & 15)] = z[0];
        }
    }
    __syncthreads();
    if (tid == 511) finish_ticket();
    const int g = lane >> 2, t = lane & 3;
    const int lr = (lane & 7) + ((lane >> 3) & 1) * 8, lc = lane >> 4;
    const uint32_t loff = (warp * 16 + lr) * 32 + ((lc ^ ((lr & 7) >> 2)) << 4);
#pragma unroll 1
    for (int quad = 0; quad < 2; quad++) {
        uint32_t bf[4][6];
#pragma unroll
        for (int j = 0; j < 4; j++) {
            const float* kv = skv + (quad * 4 + j) * 272;
            bf[j][0] = pack_bf16(kv[(2 * t) * 16 + g], kv[(2 * t + 1) * 16 + g]);
            bf[j][1] = pack_bf16(kv[(2 * t + 8) * 16 + g], kv[(2 * t + 9) * 16 + g]);
            bf[j][2] = pack_bf16(kv[(2 * t) * 16 + 8 + g], kv[(2 * t + 1) * 16 + 8 + g]);
            bf[j][3] = pack_bf16(kv[(2 * t + 8) * 16 + 8 + g], kv[(2 * t + 9) * 16 + 8 + g]);
            bf[j][4] = pack_bf16(kv[256 + 2 * t], kv[256 + 2 * t + 1]);
            bf[j][5] = pack_bf16(kv[256 + 2 * t + 8], kv[256 + 2 * t + 9]);
        }
#pragma unroll 1
        for (int rc = 0; rc < 8; rc++) {
            const int c = quad * 8 + rc;
            mbar_wait(sBar + 8 * (c % NBUF), (c / NBUF) & 1);
            const uint32_t qb = sQ0 + (c % NBUF) * 32768 + loff;
            const uint32_t stg = sSt + (c & 1) * 32768 + warp * 2048;
            uint32_t a[4][4];
#pragma unroll
            for (int j = 0; j < 4; j++) ldsm_x4(qb + j * 8192, a[j]);
            __syncwarp();
            if (lane == 0) {
                mbar_arrive(sBar + 64 + 8 * (c % NBUF));
                if (c >= 1 && warp == (c & 15) && c - 1 + NBUF < 16) {
                    const int cp = c - 1;
                    mbar_wait(sBar + 64 + 8 * (cp % NBUF), (cp / NBUF) & 1);
                    mbar_expect_tx(sBar + 8 * (cp % NBUF), 32768);
                    for (int j = 0; j < 4; j++) load_chunk(cp + NBUF, j);
                }
                if (c >= 2) asm volatile("cp.async.bulk.wait_group.read 1;" ::: "memory");
            }
            __syncwarp();
#pragma unroll
            for (int j = 0; j < 4; j++) {
#pragma unroll
                for (int i = 0; i < 4; i++) a[j][i] = phi_bf16x2(a[j][i]);
                float n0[4] = {0.f, 0.f, 0.f, 0.f}, n1[4] = {0.f, 0.f, 0.f, 0.f}, dn[4] = {0.f, 0.f, 0.f, 0.f};
                mma_bf16(n0, a[j], bf[j][0], bf[j][1]);
                mma_bf16(n1, a[j], bf[j][2], bf[j][3]);
                mma_bf16(dn, a[j], bf[j][4], bf[j][5]);
                const float i0 = rcp_fast(dn[0] + 1e-6f), i1 = rcp_fast(dn[2] + 1e-6f);
                stsm_x4(stg + lr * 128 + (((j * 2 + lc) ^ (lr & 7)) << 4),
                        pack_bf16(n0[0] * i0, n0[1] * i0), pack_bf16(n0[2] * i1, n0[3] * i1),
                        pack_bf16(n1[0] * i0, n1[1] * i0), pack_bf16(n1[2] * i1, n1[3] * i1));
            }
            fence_async_smem();
            __syncwarp();
            if (lane == 0) {
                tma_store_2d(tmO16, stg, cta * 128 + quad * 64, rc * 256 + warp * 16);
                bulk_commit();
            }
        }
    }
    if (lane == 0) { bulk_wait0(); fence_async_all(); }
    __syncthreads();
    if (tid == 0) signal_add(&g_cnt.oA);
}

__global__ void __launch_bounds__(512, 1) fused_kernel(const __grid_constant__ Maps mp) {
    extern __shared__ __align__(1024) uint8_t smem[];
    if (smem_u32(smem) != SM_BASE) __trap();
    if (blockIdx.x >= 128) {
        linattn_mid(smem, blockIdx.x - 128, &mp.o16);
    } else {
        phase_qkv(smem, mp);
        phase_attn(smem, mp);
        phase_out(smem, mp);
    }
}

typedef CUresult (*EncodeFn)(CUtensorMap*, CUtensorMapDataType, cuuint32_t, void*, const cuuint64_t*, const cuuint64_t*,
                             const cuuint32_t*, const cuuint32_t*, CUtensorMapInterleave, CUtensorMapSwizzle,
                             CUtensorMapL2promotion, CUtensorMapFloatOOBfill);

void make_map(EncodeFn enc, CUtensorMap* tm, const void* ptr, uint64_t cols, uint64_t rows, uint32_t boxc, uint32_t boxr) {
    cuuint64_t dims[2] = {cols, rows};
    cuuint64_t strides[1] = {cols * 2};
    cuuint32_t box[2] = {boxc, boxr};
    cuuint32_t es[2] = {1, 1};
    enc(tm, CU_TENSOR_MAP_DATA_TYPE_BFLOAT16, 2, const_cast<void*>(ptr), dims, strides, box, es, CU_TENSOR_MAP_INTERLEAVE_NONE,
        CU_TENSOR_MAP_SWIZZLE_128B, CU_TENSOR_MAP_L2_PROMOTION_L2_256B, CU_TENSOR_MAP_FLOAT_OOB_FILL_NONE);
}

struct HostState {
    bool init;
    const void* key[7];
    Maps mp;
};
HostState g_hs;

}

extern "C" void kernel_launch(void* const* d_in, const int* in_sizes, int n_in, void* d_out, int out_size) {
    (void)in_sizes; (void)n_in; (void)out_size;
    HostState& hs = g_hs;
    bool same = hs.init && hs.key[6] == d_out;
    for (int i = 0; i < 6 && same; i++) same = hs.key[i] == d_in[i];
    if (!same) {
        void* fn = nullptr;
        cudaDriverEntryPointQueryResult qr;
        cudaGetDriverEntryPoint("cuTensorMapEncodeTiled", &fn, cudaEnableDefault, &qr);
        EncodeFn enc = (EncodeFn)fn;
        void* po = nullptr;
        cudaGetSymbolAddress(&po, g_o);
        make_map(enc, &hs.mp.xA, d_in[0], 512, 2048, 64, 128);
        make_map(enc, &hs.mp.wA, d_in[1], 1536, 512, 64, 64);
        make_map(enc, &hs.mp.woA, d_in[2], 512, 512, 64, 64);
        make_map(enc, &hs.mp.xB, d_in[3], 512, 2048, 64, 128);
        make_map(enc, &hs.mp.wB, d_in[4], 1536, 512, 64, 64);
        make_map(enc, &hs.mp.woB, d_in[5], 512, 512, 64, 64);
        make_map(enc, &hs.mp.o, po, 1024, 2048, 64, 128);
        make_map(enc, &hs.mp.o16, po, 1024, 2048, 64, 16);
        make_map(enc, &hs.mp.out, d_out, 1024, 2048, 64, 64);
        cudaFuncSetAttribute(fused_kernel, cudaFuncAttributeMaxDynamicSharedMemorySize, SMEM_BYTES);
        for (int i = 0; i < 6; i++) hs.key[i] = d_in[i];
        hs.key[6] = d_out;
        hs.init = true;
    }
    fused_kernel<<<132, 512, SMEM_BYTES, cudaStreamPerThread>>>(hs.mp);
}
```

```cpp
#include <cuda_runtime.h>
#include <cuda_bf16.h>
#include <cuda.h>
#include <stdint.h>

namespace {

constexpr int S_LEN = 2048;
constexpr int NH = 32;

__device__ __align__(1024) uint16_t g_qB[NH * S_LEN * 16];
__device__ __align__(1024) uint16_t g_kB[NH * S_LEN * 16];
__device__ __align__(1024) uint16_t g_vB[NH * S_LEN * 16];
__device__ __align__(1024) uint16_t g_qA[NH * S_LEN * 16];
__device__ __align__(1024) uint16_t g_o[S_LEN * 1024];
__device__ __align__(16) float g_kvp[16 * NH * 272];
__device__ __align__(64) float g_qn[NH * 16];
__device__ __align__(64) float g_kn[NH * 16];

struct Counters {
    int qkvB[8];
    int qkvA[8];
    int oB[16 * 8];
    int oA;
    int done;
};
__device__ Counters g_cnt;


__device__ __forceinline__ uint32_t smem_u32(const void* p) { return (uint32_t)__cvta_generic_to_shared(p); }
__device__ __forceinline__ void wg_fence() { asm volatile("wgmma.fence.sync.aligned;" ::: "memory"); }
__device__ __forceinline__ void wg_commit() { asm volatile("wgmma.commit_group.sync.aligned;" ::: "memory"); }
template <int N> __device__ __forceinline__ void wg_wait() { asm volatile("wgmma.wait_group.sync.aligned %0;" ::"n"(N) : "memory"); }
__device__ __forceinline__ void mbar_init(uint32_t bar, uint32_t cnt) { asm volatile("mbarrier.init.shared::cta.b64 [%0], %1;" ::"r"(bar), "r"(cnt)); }
__device__ __forceinline__ void mbar_expect_tx(uint32_t bar, uint32_t bytes) {
    asm volatile("mbarrier.arrive.expect_tx.shared::cta.b64 _, [%0], %1;" ::"r"(bar), "r"(bytes) : "memory");
}
__device__ __forceinline__ void mbar_wait(uint32_t bar, uint32_t parity) {
    asm volatile(
        "{.reg .pred p;\n"
        "WAIT_LOOP:\n"
        "mbarrier.try_wait.parity.shared::cta.b64 p, [%0], %1;\n"
        "@p bra WAIT_DONE;\n"
        "bra WAIT_LOOP;\n"
        "WAIT_DONE:\n}" ::"r"(bar), "r"(parity) : "memory");
}
__device__ __forceinline__ void mbar_arrive(uint32_t bar) { asm volatile("mbarrier.arrive.shared::cta.b64 _, [%0];" ::"r"(bar) : "memory"); }
__device__ __forceinline__ void fence_mbar_init() { asm volatile("fence.mbarrier_init.release.cluster;" ::: "memory"); }
__device__ __forceinline__ void fence_async_smem() { asm volatile("fence.proxy.async.shared::cta;" ::: "memory"); }
constexpr int SPIN_NS = 100;
__device__ __forceinline__ void spin_ge(const int* p, int target) {
    int it = 0;
    while (true) {
        int v;
        asm volatile("ld.acquire.gpu.global.s32 %0, [%1];" : "=r"(v) : "l"(p) : "memory");
        if (v >= target) break;
        if (++it > (1 << 22)) __trap();
        __nanosleep(SPIN_NS);
    }
}
__device__ __forceinline__ void finish_ticket() {
    if (atomicAdd(&g_cnt.done, 1) == (int)gridDim.x - 1) {
        int* c = (int*)&g_cnt;
        for (int i = 0; i < (int)(sizeof(Counters) / sizeof(int)); i++) c[i] = 0;
    }
}
__device__ __forceinline__ void signal_add(int* p) { asm volatile("red.release.gpu.global.add.s32 [%0], 1;" ::"l"(p) : "memory"); }
__device__ __forceinline__ void fence_async_all() { asm volatile("fence.proxy.async.global;" ::: "memory"); }
__device__ __forceinline__ void named_bar(int id, int n) { asm volatile("bar.sync %0, %1;" ::"r"(id), "r"(n) : "memory"); }

__device__ __forceinline__ void bulk_g2s(uint32_t dst, const void* src, uint32_t bytes, uint32_t bar) {
    asm volatile("cp.async.bulk.shared::cluster.global.mbarrier::complete_tx::bytes [%0], [%1], %2, [%3];" ::"r"(dst), "l"(src), "r"(bytes), "r"(bar) : "memory");
}
__device__ __forceinline__ void bulk_commit() { asm volatile("cp.async.bulk.commit_group;" ::: "memory"); }
__device__ __forceinline__ void bulk_wait0() { asm volatile("cp.async.bulk.wait_group 0;" ::: "memory"); }
__device__ __forceinline__ void tma_load_2d(uint32_t dst, const CUtensorMap* tm, int c0, int c1, uint32_t bar) {
    asm volatile("cp.async.bulk.tensor.2d.shared::cluster.global.mbarrier::complete_tx::bytes [%0], [%1, {%3, %4}], [%2];" ::"r"(dst), "l"(tm), "r"(bar), "r"(c0), "r"(c1) : "memory");
}
__device__ __forceinline__ void tma_store_2d(const CUtensorMap* tm, uint32_t src, int c0, int c1) {
    asm volatile("cp.async.bulk.tensor.2d.global.shared::cta.bulk_group [%0, {%2, %3}], [%1];" ::"l"(tm), "r"(src), "r"(c0), "r"(c1) : "memory");
}
__device__ __forceinline__ void tma_prefetch_desc(const CUtensorMap* tm) { asm volatile("prefetch.tensormap [%0];" ::"l"(tm) : "memory"); }

__device__ __forceinline__ uint32_t pack_bf16(float lo, float hi) {
    uint32_t r; asm("cvt.rn.bf16x2.f32 %0, %1, %2;" : "=r"(r) : "f"(hi), "f"(lo)); return r;
}
__device__ __forceinline__ float ex2f(float x) { float r; asm("ex2.approx.ftz.f32 %0, %1;" : "=f"(r) : "f"(x)); return r; }
__device__ __forceinline__ float bf_lo(uint32_t p) { return __uint_as_float(p << 16); }
__device__ __forceinline__ float bf_hi(uint32_t p) { return __uint_as_float(p & 0xFFFF0000u); }
__device__ __forceinline__ void stsm_x4(uint32_t addr, uint32_t r0, uint32_t r1, uint32_t r2, uint32_t r3) {
    asm volatile("stmatrix.sync.aligned.m8n8.x4.shared.b16 [%0], {%1,%2,%3,%4};" ::"r"(addr), "r"(r0), "r"(r1), "r"(r2), "r"(r3) : "memory");
}
__device__ __forceinline__ void ldsm_x4(uint32_t addr, uint32_t* r) {
    asm volatile("ldmatrix.sync.aligned.m8n8.x4.shared.b16 {%0,%1,%2,%3}, [%4];" : "=r"(r[0]), "=r"(r[1]), "=r"(r[2]), "=r"(r[3]) : "r"(addr) : "memory");
}
__device__ __forceinline__ void ldsm_x4_t(uint32_t addr, uint32_t* r) {
    asm volatile("ldmatrix.sync.aligned.m8n8.x4.trans.shared.b16 {%0,%1,%2,%3}, [%4];" : "=r"(r[0]), "=r"(r[1]), "=r"(r[2]), "=r"(r[3]) : "r"(addr) : "memory");
}
__device__ __forceinline__ void mma_bf16(float* d, const uint32_t* a, uint32_t b0, uint32_t b1) {
    asm volatile("mma.sync.aligned.m16n8k16.row.col.f32.bf16.bf16.f32 {%0,%1,%2,%3}, {%4,%5,%6,%7}, {%8,%9}, {%0,%1,%2,%3};"
                 : "+f"(d[0]), "+f"(d[1]), "+f"(d[2]), "+f"(d[3]) : "r"(a[0]), "r"(a[1]), "r"(a[2]), "r"(a[3]), "r"(b0), "r"(b1));
}
__device__ __forceinline__ uint32_t phi_bf16x2(uint32_t p) {
    const float t0 = bf_lo(p), t1 = bf_hi(p);
    const float a0 = fmaf(t0 + fabsf(t0), 0.5f, ex2f((t0 - fabsf(t0)) * 0.7213475204444817f));
    const float a1 = fmaf(t1 + fabsf(t1), 0.5f, ex2f((t1 - fabsf(t1)) * 0.7213475204444817f));
    const uint32_t a = pack_bf16(a0, a1);
    uint32_t r;
    asm("add.rn.bf16x2 %0, %1, %2;" : "=r"(r) : "r"(a), "r"(0x35863586u));
    return r;
}
__device__ __forceinline__ float rcp_fast(float x) { float r; asm("rcp.approx.ftz.f32 %0, %1;" : "=f"(r) : "f"(x)); return r; }
template <typename T, int N> __device__ __forceinline__ void fence_regs(T (&r)[N]) {
#pragma unroll
    for (int i = 0; i < N; i++) {
        if constexpr (sizeof(T) == 4 && T(0.5) != T(0)) asm volatile("" : "+f"(r[i])::"memory");
        else asm volatile("" : "+r"(r[i])::"memory");
    }
}

__device__ __forceinline__ void wgmma_ss_n192_tb(float* d, uint64_t da, uint64_t db, int sd) {
  asm volatile("{.reg .pred p; setp.ne.b32 p, %98, 0; wgmma.mma_async.sync.aligned.m64n192k16.f32.bf16.bf16 {%0,%1,%2,%3,%4,%5,%6,%7,%8,%9,%10,%11,%12,%13,%14,%15,%16,%17,%18,%19,%20,%21,%22,%23,%24,%25,%26,%27,%28,%29,%30,%31,%32,%33,%34,%35,%36,%37,%38,%39,%40,%41,%42,%43,%44,%45,%46,%47,%48,%49,%50,%51,%52,%53,%54,%55,%56,%57,%58,%59,%60,%61,%62,%63,%64,%65,%66,%67,%68,%69,%70,%71,%72,%73,%74,%75,%76,%77,%78,%79,%80,%81,%82,%83,%84,%85,%86,%87,%88,%89,%90,%91,%92,%93,%94,%95}, %96, %97, p, 1, 1, 0, 1;}"
    : "+f"(d[0]), "+f"(d[1]), "+f"(d[2]), "+f"(d[3]), "+f"(d[4]), "+f"(d[5]), "+f"(d[6]), "+f"(d[7]), "+f"(d[8]), "+f"(d[9]), "+f"(d[10]), "+f"(d[11]), "+f"(d[12]), "+f"(d[13]), "+f"(d[14]), "+f"(d[15]), "+f"(d[16]), "+f"(d[17]), "+f"(d[18]), "+f"(d[19]), "+f"(d[20]), "+f"(d[21]), "+f"(d[22]), "+f"(d[23]), "+f"(d[24]), "+f"(d[25]), "+f"(d[26]), "+f"(d[27]), "+f"(d[28]), "+f"(d[29]), "+f"(d[30]), "+f"(d[31]), "+f"(d[32]), "+f"(d[33]), "+f"(d[34]), "+f"(d[35]), "+f"(d[36]), "+f"(d[37]), "+f"(d[38]), "+f"(d[39]), "+f"(d[40]), "+f"(d[41]), "+f"(d[42]), "+f"(d[43]), "+f"(d[44]), "+f"(d[45]), "+f"(d[46]), "+f"(d[47]), "+f"(d[48]), "+f"(d[49]), "+f"(d[50]), "+f"(d[51]), "+f"(d[52]), "+f"(d[53]), "+f"(d[54]), "+f"(d[55]), "+f"(d[56]), "+f"(d[57]), "+f"(d[58]), "+f"(d[59]), "+f"(d[60]), "+f"(d[61]), "+f"(d[62]), "+f"(d[63]), "+f"(d[64]), "+f"(d[65]), "+f"(d[66]), "+f"(d[67]), "+f"(d[68]), "+f"(d[69]), "+f"(d[70]), "+f"(d[71]), "+f"(d[72]), "+f"(d[73]), "+f"(d[74]), "+f"(d[75]), "+f"(d[76]), "+f"(d[77]), "+f"(d[78]), "+f"(d[79]), "+f"(d[80]), "+f"(d[81]), "+f"(d[82]), "+f"(d[83]), "+f"(d[84]), "+f"(d[85]), "+f"(d[86]), "+f"(d[87]), "+f"(d[88]), "+f"(d[89]), "+f"(d[90]), "+f"(d[91]), "+f"(d[92]), "+f"(d[93]), "+f"(d[94]), "+f"(d[95]) : "l"(da), "l"(db), "r"(sd));
}
__device__ __forceinline__ void wgmma_ss_n128_tb(float* d, uint64_t da, uint64_t db, int sd) {
  asm volatile("{.reg .pred p; setp.ne.b32 p, %66, 0; wgmma.mma_async.sync.aligned.m64n128k16.f32.bf16.bf16 {%0,%1,%2,%3,%4,%5,%6,%7,%8,%9,%10,%11,%12,%13,%14,%15,%16,%17,%18,%19,%20,%21,%22,%23,%24,%25,%26,%27,%28,%29,%30,%31,%32,%33,%34,%35,%36,%37,%38,%39,%40,%41,%42,%43,%44,%45,%46,%47,%48,%49,%50,%51,%52,%53,%54,%55,%56,%57,%58,%59,%60,%61,%62,%63}, %64, %65, p, 1, 1, 0, 1;}"
    : "+f"(d[0]), "+f"(d[1]), "+f"(d[2]), "+f"(d[3]), "+f"(d[4]), "+f"(d[5]), "+f"(d[6]), "+f"(d[7]), "+f"(d[8]), "+f"(d[9]), "+f"(d[10]), "+f"(d[11]), "+f"(d[12]), "+f"(d[13]), "+f"(d[14]), "+f"(d[15]), "+f"(d[16]), "+f"(d[17]), "+f"(d[18]), "+f"(d[19]), "+f"(d[20]), "+f"(d[21]), "+f"(d[22]), "+f"(d[23]), "+f"(d[24]), "+f"(d[25]), "+f"(d[26]), "+f"(d[27]), "+f"(d[28]), "+f"(d[29]), "+f"(d[30]), "+f"(d[31]), "+f"(d[32]), "+f"(d[33]), "+f"(d[34]), "+f"(d[35]), "+f"(d[36]), "+f"(d[37]), "+f"(d[38]), "+f"(d[39]), "+f"(d[40]), "+f"(d[41]), "+f"(d[42]), "+f"(d[43]), "+f"(d[44]), "+f"(d[45]), "+f"(d[46]), "+f"(d[47]), "+f"(d[48]), "+f"(d[49]), "+f"(d[50]), "+f"(d[51]), "+f"(d[52]), "+f"(d[53]), "+f"(d[54]), "+f"(d[55]), "+f"(d[56]), "+f"(d[57]), "+f"(d[58]), "+f"(d[59]), "+f"(d[60]), "+f"(d[61]), "+f"(d[62]), "+f"(d[63]) : "l"(da), "l"(db), "r"(sd));
}
template<int SD> __device__ __forceinline__ void wgmma_rs_n64(float* d, const uint32_t* a, uint64_t db) {
  asm volatile("{.reg .pred p; setp.ne.b32 p, %37, 0; wgmma.mma_async.sync.aligned.m64n64k16.f32.bf16.bf16 {%0,%1,%2,%3,%4,%5,%6,%7,%8,%9,%10,%11,%12,%13,%14,%15,%16,%17,%18,%19,%20,%21,%22,%23,%24,%25,%26,%27,%28,%29,%30,%31}, {%32,%33,%34,%35}, %36, p, 1, 1, 0;}"
    : "+f"(d[0]), "+f"(d[1]), "+f"(d[2]), "+f"(d[3]), "+f"(d[4]), "+f"(d[5]), "+f"(d[6]), "+f"(d[7]), "+f"(d[8]), "+f"(d[9]), "+f"(d[10]), "+f"(d[11]), "+f"(d[12]), "+f"(d[13]), "+f"(d[14]), "+f"(d[15]), "+f"(d[16]), "+f"(d[17]), "+f"(d[18]), "+f"(d[19]), "+f"(d[20]), "+f"(d[21]), "+f"(d[22]), "+f"(d[23]), "+f"(d[24]), "+f"(d[25]), "+f"(d[26]), "+f"(d[27]), "+f"(d[28]), "+f"(d[29]), "+f"(d[30]), "+f"(d[31]) : "r"(a[0]), "r"(a[1]), "r"(a[2]), "r"(a[3]), "l"(db), "n"(SD));
}
template<int SD> __device__ __forceinline__ void wgmma_rs_n24(float* d, const uint32_t* a, uint64_t db) {
  asm volatile("{.reg .pred p; setp.ne.b32 p, %17, 0; wgmma.mma_async.sync.aligned.m64n24k16.f32.bf16.bf16 {%0,%1,%2,%3,%4,%5,%6,%7,%8,%9,%10,%11}, {%12,%13,%14,%15}, %16, p, 1, 1, 0;}"
    : "+f"(d[0]), "+f"(d[1]), "+f"(d[2]), "+f"(d[3]), "+f"(d[4]), "+f"(d[5]), "+f"(d[6]), "+f"(d[7]), "+f"(d[8]), "+f"(d[9]), "+f"(d[10]), "+f"(d[11]) : "r"(a[0]), "r"(a[1]), "r"(a[2]), "r"(a[3]), "l"(db), "n"(SD));
}
template<int SD> __device__ __forceinline__ void wgmma_rs_n32(float* d, const uint32_t* a, uint64_t db) {
  asm volatile("{.reg .pred p; setp.ne.b32 p, %21, 0; wgmma.mma_async.sync.aligned.m64n32k16.f32.bf16.bf16 {%0,%1,%2,%3,%4,%5,%6,%7,%8,%9,%10,%11,%12,%13,%14,%15}, {%16,%17,%18,%19}, %20, p, 1, 1, 0;}"
    : "+f"(d[0]), "+f"(d[1]), "+f"(d[2]), "+f"(d[3]), "+f"(d[4]), "+f"(d[5]), "+f"(d[6]), "+f"(d[7]), "+f"(d[8]), "+f"(d[9]), "+f"(d[10]), "+f"(d[11]), "+f"(d[12]), "+f"(d[13]), "+f"(d[14]), "+f"(d[15]) : "r"(a[0]), "r"(a[1]), "r"(a[2]), "r"(a[3]), "l"(db), "n"(SD));
}
template<int SD> __device__ __forceinline__ void wgmma_rs_n40(float* d, const uint32_t* a, uint64_t db) {
  asm volatile("{.reg .pred p; setp.ne.b32 p, %25, 0; wgmma.mma_async.sync.aligned.m64n40k16.f32.bf16.bf16 {%0,%1,%2,%3,%4,%5,%6,%7,%8,%9,%10,%11,%12,%13,%14,%15,%16,%17,%18,%19}, {%20,%21,%22,%23}, %24, p, 1, 1, 0;}"
    : "+f"(d[0]), "+f"(d[1]), "+f"(d[2]), "+f"(d[3]), "+f"(d[4]), "+f"(d[5]), "+f"(d[6]), "+f"(d[7]), "+f"(d[8]), "+f"(d[9]), "+f"(d[10]), "+f"(d[11]), "+f"(d[12]), "+f"(d[13]), "+f"(d[14]), "+f"(d[15]), "+f"(d[16]), "+f"(d[17]), "+f"(d[18]), "+f"(d[19]) : "r"(a[0]), "r"(a[1]), "r"(a[2]), "r"(a[3]), "l"(db), "n"(SD));
}
template<int SD> __device__ __forceinline__ void wgmma_rs_n24_tb(float* d, const uint32_t* a, uint64_t db) {
  asm volatile("{.reg .pred p; setp.ne.b32 p, %17, 0; wgmma.mma_async.sync.aligned.m64n24k16.f32.bf16.bf16 {%0,%1,%2,%3,%4,%5,%6,%7,%8,%9,%10,%11}, {%12,%13,%14,%15}, %16, p, 1, 1, 1;}"
    : "+f"(d[0]), "+f"(d[1]), "+f"(d[2]), "+f"(d[3]), "+f"(d[4]), "+f"(d[5]), "+f"(d[6]), "+f"(d[7]), "+f"(d[8]), "+f"(d[9]), "+f"(d[10]), "+f"(d[11]) : "r"(a[0]), "r"(a[1]), "r"(a[2]), "r"(a[3]), "l"(db), "n"(SD));
}

constexpr uint64_t DESC_SW128 = (uint64_t)1 << 62;
constexpr uint64_t DESC_SW32 = (uint64_t)3 << 62;
__device__ __forceinline__ uint64_t mk_desc(uint64_t sw, uint32_t addr, uint32_t lbo, uint32_t sbo) {
    return sw | ((uint64_t)(sbo >> 4) << 32) | ((uint64_t)(lbo >> 4) << 16) | (uint64_t)((addr & 0x3FFFF) >> 4);
}

constexpr uint32_t SM_BASE = 1024;
constexpr uint32_t P1_STAGE = 40960;
constexpr uint32_t P1_STGA = 98304;
constexpr uint32_t P1_RED = 147456;
constexpr uint32_t AT_Q = 0, AT_K = 16384, AT_V = 81920, AT_TAB = 163840, AT_CT = 230400, AT_ONES = 230912;
constexpr uint32_t P3_O = AT_TAB;
constexpr uint32_t BAR = 229376;
constexpr uint32_t B_FULL = BAR, B_EMPTY = BAR + 32;
constexpr uint32_t B_KV = BAR + 96, B_Q = BAR + 160, B_CONS = BAR + 168, B_WFULL = BAR + 232, B_OFULL = BAR + 296, B_OEMPTY = BAR + 328;
constexpr uint32_t B_STFREE = BAR + 360;
constexpr uint32_t OFF_MAX = BAR + 416, OFF_NORM = BAR + 512;
constexpr int SMEM_BYTES = AT_CT + 1280;
constexpr uint32_t B_TAB = BAR + 64;
constexpr float QSCALE = 0.25f * 1.4426950408889634f;

struct Maps { CUtensorMap xA, xB, wA, wB, o, o16, woA, woB, out; };

__device__ __forceinline__ void phase_qkv(uint8_t* smem, const Maps& mp) {
    constexpr uint32_t sb = SM_BASE;
    const int tid = threadIdx.x, warp = tid >> 5, lane = tid & 31;
    const int nt = blockIdx.x & 7, mt = blockIdx.x >> 3;
    float* sMax = (float*)(smem + OFF_MAX);
    auto produce = [&](int kb) {
        const int s = kb & 3;
        const uint32_t full = sb + B_FULL + 8 * s, st = sb + s * P1_STAGE;
        mbar_expect_tx(full, P1_STAGE);
        tma_load_2d(st, kb < 8 ? &mp.xB : &mp.xA, (kb & 7) * 64, mt * 128, full);
#pragma unroll
        for (int j = 0; j < 3; j++) tma_load_2d(st + 16384 + j * 8192, kb < 8 ? &mp.wB : &mp.wA, j * 512 + nt * 64, (kb & 7) * 64, full);
    };
    if (tid == 0) {
        tma_prefetch_desc(&mp.xB); tma_prefetch_desc(&mp.wB);
        for (int i = 0; i < 4; i++) { mbar_init(sb + B_FULL + 8 * i, 1); mbar_init(sb + B_EMPTY + 8 * i, 2); }
        fence_mbar_init();
        for (int kb = 0; kb < 4; kb++) produce(kb);
        tma_prefetch_desc(&mp.xA); tma_prefetch_desc(&mp.wA);
    }
    if (tid == 32) {
        for (int i = 0; i < 4; i++) mbar_init(sb + B_STFREE + 8 * i, 2);
        mbar_init(sb + B_Q, 1); mbar_init(sb + B_TAB, 256);
        for (int i = 0; i < 8; i++) { mbar_init(sb + B_KV + 8 * i, 1); mbar_init(sb + B_CONS + 8 * i, 4); mbar_init(sb + B_WFULL + 8 * i, 1); }
        for (int i = 0; i < 4; i++) { mbar_init(sb + B_OFULL + 8 * i, 1); mbar_init(sb + B_OEMPTY + 8 * i, 2); }
        fence_mbar_init();
    }
    if (tid >= 64 && tid < 72) sMax[tid - 64] = 0.f;
    __syncthreads();

    const int wg = __shfl_sync(0xffffffffu, warp >> 2, 0);
    const int branchB = wg < 2;
    const int wh = wg & 1;
    const int kb0 = branchB ? 0 : 8;
    float acc[96];
#pragma unroll
    for (int i = 0; i < 96; i++) acc[i] = 0.f;
    fence_regs(acc);
    if (!branchB) {
        const int w = warp & 7, j = w * 32 + lane;
        const float f = (j + 0.5f) * (1.f / 256.f);
        const uint32_t val = (uint32_t)(__float2int_rn((exp2f(f) - 1.f) * 128.f) - (j >> 1) + (63 << 7) - 0x8000);
        uint4* tb = (uint4*)(smem + AT_TAB) + w * 32 * 8 + lane;
#pragma unroll
        for (int i = 0; i < 8; i++) {
            const uint32_t v = __shfl_sync(0xffffffffu, val, i * 4 + (lane >> 3));
            tb[i * 32] = make_uint4(v, v, v, v);
            tb[2048 + i * 32] = make_uint4(v << 16, v << 16, v << 16, v << 16);
        }
        if (w == 0) { for (int i = lane; i < 128; i += 32) ((uint32_t*)(smem + AT_ONES))[i] = 0x3F803F80u; }
        if (w == 1) {
            for (int i = lane; i < 64; i += 32) {
                const int r = i >> 3, ww = i & 7, chunk = (ww >> 2) ^ (r >> 2);
                ((uint32_t*)(smem + AT_CT))[i] = (chunk == 0 && (ww & 3) == 0) ? 0x000043A0u : 0u;
            }
        }
        if (w == 2 && lane < 8) ((uint32_t*)(smem + AT_CT + 256))[lane] = lane < 2 ? 0x00003F80u : 0u;
        fence_async_smem();
        mbar_arrive(sb + B_TAB);
        named_bar(3, 512);
    }
    const uint64_t dA0 = mk_desc(DESC_SW128, sb + wh * 8192, 16, 1024);
#pragma unroll
    for (int i = 0; i < 8; i++) {
        const int kb = kb0 + i, s = i & 3;
        mbar_wait(sb + B_FULL + 8 * s, (i >> 2) & 1);
        const uint64_t dA = dA0 + (uint64_t)(s * (P1_STAGE >> 4)), dB = mk_desc(DESC_SW128, sb + s * P1_STAGE + 16384, 8192, 1024);
        wg_fence();
#pragma unroll
        for (int k = 0; k < 4; k++) wgmma_ss_n192_tb(acc, dA + k * 2, dB + k * 128, 1);
        wg_commit();
        if (i == 7 && branchB) asm volatile("bar.arrive 3, 512;" ::: "memory");
        if (i > 0) {
            wg_wait<1>();
            if (i >= 5 && !branchB && (tid & 127) == 0) mbar_arrive(sb + B_STFREE + 8 * (i - 5));
            if (kb + 3 < 16) {
                const uint32_t eb = sb + B_EMPTY + 8 * ((i - 1) & 3);
                if ((tid & 127) == 0) {
                    mbar_arrive(eb);
                    if (wh == 0) { mbar_wait(eb, ((i - 1) >> 2) & 1); produce(kb + 3); }
                }
                __syncwarp();
            }
        }
    }
    wg_wait<0>();
    fence_regs(acc);

    const int wq = warp & 3, g = lane >> 2, t = lane & 3;
    const int lr = (lane & 7) + ((lane >> 3) & 1) * 8;
    const int lc = lane >> 4;
    const int row0 = mt * 128;
    const int w8 = warp & 7;
    if (branchB) {
        {
            const uint32_t eb = sb + B_EMPTY + 8 * 3;
            if ((tid & 127) == 0) {
                mbar_arrive(eb);
                if (wh == 0) { mbar_wait(eb, 1); produce(11); }
            }
            __syncwarp();
        }
        const int orow = g + (t >> 1) * 8;
        const uint32_t ooff = (uint32_t)(row0 + wh * 64 + wq * 16 + orow) * 32 + (((t & 1) ^ ((orow & 7) >> 2)) << 4);
        const bool o1 = t & 1, o2 = t & 2;
        uint32_t mymax = 0;
#pragma unroll
        for (int sl = 0; sl < 12; sl++) {
            float* a = acc + sl * 8;
            if (sl < 4) {
#pragma unroll
                for (int i = 0; i < 8; i++) a[i] *= QSCALE;
            }
            if (sl < 8) {
                const float n0 = fmaf(a[0], a[0], fmaf(a[1], a[1], fmaf(a[4], a[4], a[5] * a[5])));
                const float n1 = fmaf(a[2], a[2], fmaf(a[3], a[3], fmaf(a[6], a[6], a[7] * a[7])));
                const uint32_t m = __reduce_max_sync(0xffffffffu, __float_as_uint(fmaxf(n0, n1)));
                if (lane == sl) mymax = m;
            }
            const uint32_t w0 = pack_bf16(a[0], a[1]), w2 = pack_bf16(a[2], a[3]), w1 = pack_bf16(a[4], a[5]), w3 = pack_bf16(a[6], a[7]);
            const uint32_t r0 = __shfl_xor_sync(0xffffffffu, o1 ? w0 : w1, 1), r1 = __shfl_xor_sync(0xffffffffu, o1 ? w2 : w3, 1);
            const uint32_t x0 = o1 ? r0 : w0, x1 = o1 ? w1 : r0, y0 = o1 ? r1 : w2, y1 = o1 ? w3 : r1;
            const uint32_t q0 = __shfl_xor_sync(0xffffffffu, o2 ? x0 : y0, 2), q1 = __shfl_xor_sync(0xffffffffu, o2 ? x1 : y1, 2);
            uint4 val;
            val.x = o2 ? q0 : x0; val.y = o2 ? q1 : x1; val.z = o2 ? y0 : q0; val.w = o2 ? y1 : q1;
            const int ty = sl >> 2, head = nt * 4 + (sl & 3);
            uint8_t* dst = (uint8_t*)((ty == 0 ? g_qB : (ty == 1 ? g_kB : g_vB)) + (size_t)head * S_LEN * 16);
            *(uint4*)(dst + ooff) = val;
        }
        if (lane < 8) atomicMax((unsigned int*)&sMax[lane], mymax);
        named_bar(1, 256);
        if (w8 == 7 && lane >= 8 && lane < 16) { const int i = lane - 8; (i < 4 ? g_qn : g_kn)[(nt * 4 + (i & 3)) * 16 + mt] = sMax[i]; }
        named_bar(1, 256);
        const int h = blockIdx.x >> 2, qb = blockIdx.x & 3;
        if (tid == 0) signal_add(&g_cnt.qkvB[nt]);
        auto ld_k = [&](int c) {
            mbar_expect_tx(sb + B_KV + 8 * c, 16384);
            bulk_g2s(sb + AT_K + c * 8192, g_kB + ((size_t)h * S_LEN + c * 256) * 16, 8192, sb + B_KV + 8 * c);
        };
        auto ld_v = [&](int c) { bulk_g2s(sb + AT_V + c * 8192, g_vB + ((size_t)h * S_LEN + c * 256) * 16, 8192, sb + B_KV + 8 * c); };
        if (tid == 32) {
            spin_ge(&g_cnt.qkvB[h >> 2], 16);
            fence_async_all();
            mbar_wait(sb + B_STFREE, 0);
            mbar_expect_tx(sb + B_Q, 16384 + 128);
            bulk_g2s(sb + AT_Q, g_qB + ((size_t)h * S_LEN + qb * 512) * 16, 16384, sb + B_Q);
            ld_k(0);
            bulk_g2s(sb + OFF_NORM, g_qn + h * 16, 64, sb + B_Q);
            bulk_g2s(sb + OFF_NORM + 64, g_kn + h * 16, 64, sb + B_Q);
            mbar_wait(sb + B_STFREE + 16, 0);
            ld_v(0); ld_k(1); ld_v(1);
        }
        __syncwarp();
    } else {
        if ((tid & 127) == 0) mbar_arrive(sb + B_STFREE + 8 * 3);
        named_bar(2, 256);
        const uint32_t stg = sb + P1_STGA;
        const uint32_t stAddr = stg + (wh * 64 + wq * 16 + lr) * 32 + (((lc ^ ((lr & 7) >> 2))) << 4);
#pragma unroll
        for (int sl = 0; sl < 12; sl++) {
            float* a = acc + sl * 8;
            uint32_t p0 = pack_bf16(a[0], a[1]), p1 = pack_bf16(a[2], a[3]), p2 = pack_bf16(a[4], a[5]), p3 = pack_bf16(a[6], a[7]);
            if (sl >= 4 && sl < 8) { p0 = phi_bf16x2(p0); p1 = phi_bf16x2(p1); p2 = phi_bf16x2(p2); p3 = phi_bf16x2(p3); }
            stsm_x4(stAddr + sl * 4096, p0, p1, p2, p3);
        }
        named_bar(2, 256);
#pragma unroll
        for (int sl = 0; sl < 4; sl++)
            *(uint4*)((uint8_t*)(g_qA + ((size_t)(nt * 4 + sl) * S_LEN + row0) * 16) + (tid - 256) * 16) = *(const uint4*)(smem + P1_STGA + sl * 4096 + (tid - 256) * 16);
        const int hh = w8 & 3;
        const uint32_t pkb = stg + (4 + hh) * 4096 + wh * 2048, vb = stg + (8 + hh) * 4096 + wh * 2048;
        float kv0[4] = {0.f, 0.f, 0.f, 0.f}, kv1[4] = {0.f, 0.f, 0.f, 0.f}, zz[4] = {0.f, 0.f, 0.f, 0.f};
        const int ar = (lane & 7) + (lane >> 4) * 8, ac = (lane >> 3) & 1;
        const int br = (lane & 7) + ((lane >> 3) & 1) * 8, bc = lane >> 4;
#pragma unroll
        for (int ks = 0; ks < 4; ks++) {
            uint32_t af[4], bf[4];
            ldsm_x4_t(pkb + (ks * 16 + ar) * 32 + ((ac ^ ((ar & 7) >> 2)) << 4), af);
            ldsm_x4_t(vb + (ks * 16 + br) * 32 + ((bc ^ ((br & 7) >> 2)) << 4), bf);
            mma_bf16(kv0, af, bf[0], bf[1]);
            mma_bf16(kv1, af, bf[2], bf[3]);
            mma_bf16(zz, af, 0x3F803F80u, 0x3F803F80u);
        }
        float* rp = (float*)(smem + P1_RED) + hh * 272;
        if (wh == 1) {
            rp[g * 16 + 2 * t] = kv0[0]; rp[g * 16 + 2 * t + 1] = kv0[1];
            rp[(g + 8) * 16 + 2 * t] = kv0[2]; rp[(g + 8) * 16 + 2 * t + 1] = kv0[3];
            rp[g * 16 + 8 + 2 * t] = kv1[0]; rp[g * 16 + 8 + 2 * t + 1] = kv1[1];
            rp[(g + 8) * 16 + 8 + 2 * t] = kv1[2]; rp[(g + 8) * 16 + 8 + 2 * t + 1] = kv1[3];
            if (t == 0) { rp[256 + g] = zz[0]; rp[256 + g + 8] = zz[2]; }
        }
        named_bar(2, 256);
        if (wh == 0) {
            float* gp = g_kvp + (size_t)(mt * NH + nt * 4 + hh) * 272;
            *(float2*)(gp + g * 16 + 2 * t) = make_float2(kv0[0] + rp[g * 16 + 2 * t], kv0[1] + rp[g * 16 + 2 * t + 1]);
            *(float2*)(gp + (g + 8) * 16 + 2 * t) = make_float2(kv0[2] + rp[(g + 8) * 16 + 2 * t], kv0[3] + rp[(g + 8) * 16 + 2 * t + 1]);
            *(float2*)(gp + g * 16 + 8 + 2 * t) = make_float2(kv1[0] + rp[g * 16 + 8 + 2 * t], kv1[1] + rp[g * 16 + 8 + 2 * t + 1]);
            *(float2*)(gp + (g + 8) * 16 + 8 + 2 * t) = make_float2(kv1[2] + rp[(g + 8) * 16 + 8 + 2 * t], kv1[3] + rp[(g + 8) * 16 + 8 + 2 * t + 1]);
            if (t == 0) { gp[256 + g] = zz[0] + rp[256 + g]; gp[256 + g + 8] = zz[2] + rp[256 + g + 8]; }
        }
    }
}

constexpr int AT_NT = 64;
constexpr int AT_NP = 32, AT_NP2 = 40;
constexpr float AT_SAFE2 = 56.f * 56.f;

__device__ __forceinline__ uint32_t ex2_tab2(float ya, float yb, uint32_t lane4) {
    const uint32_t a = __float_as_uint(ya), b = __float_as_uint(yb);
    uint32_t aa, ab, ta, tb, L;
    asm("lop3.b32 %0, %1, 0x7F80, %2, 0xEA;" : "=r"(aa) : "r"(a), "r"(lane4));
    asm("lop3.b32 %0, %1, 0x7F80, %2, 0xEA;" : "=r"(ab) : "r"(b), "r"(lane4));
    asm volatile("ld.shared.u32 %0, [%1+%2];" : "=r"(ta) : "r"(aa), "n"(SM_BASE + AT_TAB));
    asm volatile("ld.shared.u32 %0, [%1+%2];" : "=r"(tb) : "r"(ab), "n"(SM_BASE + AT_TAB + 32768));
    asm("prmt.b32 %0, %1, %2, 0x6521;" : "=r"(L) : "r"(a), "r"(b));
    return L + ta + tb;
}
template <int NT, int NP>
__device__ __forceinline__ void att_exp(const float* s, uint32_t* p, uint32_t lane4) {
    constexpr int PP = NP / 4, TOT = NT / 4;
#pragma unroll
    for (int i = 0; i < TOT; i++) {
        const int nb = (i * PP) / TOT, na = ((i + 1) * PP) / TOT;
        if (na != nb) p[nb] = ex2_tab2(s[2 * nb], s[2 * nb + 1], lane4);
        else { const int im = PP + i - nb; p[im] = pack_bf16(ex2f(s[2 * im]), ex2f(s[2 * im + 1])); }
    }
}

__device__ __forceinline__ void mbar_arrive_elect(uint32_t bar) {
    asm volatile("{.reg .pred p;\nelect.sync _|p, 0xffffffff;\n@p mbarrier.arrive.shared::cta.b64 _, [%0];\n}" ::"r"(bar) : "memory");
}
__device__ __forceinline__ void load_wo_elect(const Maps& mp, int branchB, int nt, int c) {
    constexpr uint32_t sb = SM_BASE;
    const CUtensorMap* tm = branchB ? &mp.woB : &mp.woA;
    asm volatile(
        "{.reg .pred p;\n"
        "elect.sync _|p, 0xffffffff;\n"
        "@p mbarrier.arrive.expect_tx.shared::cta.b64 _, [%0], 16384;\n"
        "@p cp.async.bulk.tensor.2d.shared::cluster.global.mbarrier::complete_tx::bytes [%1], [%3, {%4, %6}], [%0];\n"
        "@p cp.async.bulk.tensor.2d.shared::cluster.global.mbarrier::complete_tx::bytes [%2], [%3, {%5, %6}], [%0];\n"
        "}" ::"r"(sb + B_WFULL + 8 * c), "r"(sb + AT_K + c * 8192), "r"(sb + AT_V + c * 8192), "l"(tm), "r"(nt * 128), "r"(nt * 128 + 64), "r"(c * 64)
        : "memory");
}
__device__ __forceinline__ void load_kv_elect(int h, int c) {
    constexpr uint32_t sb = SM_BASE;
    asm volatile(
        "{.reg .pred p;\n"
        "elect.sync _|p, 0xffffffff;\n"
        "@p mbarrier.arrive.expect_tx.shared::cta.b64 _, [%0], 16384;\n"
        "@p cp.async.bulk.shared::cluster.global.mbarrier::complete_tx::bytes [%1], [%3], 8192, [%0];\n"
        "@p cp.async.bulk.shared::cluster.global.mbarrier::complete_tx::bytes [%2], [%4], 8192, [%0];\n"
        "}" ::"r"(sb + B_KV + 8 * c), "r"(sb + AT_K + c * 8192), "r"(sb + AT_V + c * 8192),
        "l"(g_kB + ((size_t)h * S_LEN + c * 256) * 16), "l"(g_vB + ((size_t)h * S_LEN + c * 256) * 16) : "memory");
}
__device__ __forceinline__ void load_wo(const Maps& mp, int branchB, int nt, int c) {
    constexpr uint32_t sb = SM_BASE;
    const CUtensorMap* tm = branchB ? &mp.woB : &mp.woA;
    mbar_expect_tx(sb + B_WFULL + 8 * c, 16384);
    tma_load_2d(sb + AT_K + c * 8192, tm, nt * 128, c * 64, sb + B_WFULL + 8 * c);
    tma_load_2d(sb + AT_V + c * 8192, tm, nt * 128 + 64, c * 64, sb + B_WFULL + 8 * c);
}

__device__ __forceinline__ void phase_attn(uint8_t* smem, const Maps& mp) {
    constexpr uint32_t sb = SM_BASE;
    const int tid = threadIdx.x, warp = (tid >> 5) & 3, lane = tid & 31;
    const int wg = __shfl_sync(0xffffffffu, tid >> 7, 0);
    const int wwarp = __shfl_sync(0xffffffffu, warp, 0);
    const int h = blockIdx.x >> 2, qb = blockIdx.x & 3;
    constexpr int NCH = 8;
    constexpr uint32_t sK = sb + AT_K, sV = sb + AT_V, sQ = sb + AT_Q, sBar = sb + B_KV;

    named_bar(4 + wg, 128);
    mbar_wait(sb + B_TAB, 0);
    mbar_wait(sb + B_Q, 0);
    if (wg >= 2) {
        named_bar(2, 256);
        if (wwarp < 3) load_kv_elect(h, 2 + (wg - 2) * 3 + wwarp);
    }
    __syncwarp();
    bool safe;
    {
        const float* nrm = (const float*)(smem + OFF_NORM);
        const float qv = lane < 4 ? nrm[qb * 4 + lane] : 0.f;
        const float kv = lane < 16 ? nrm[16 + lane] : 0.f;
        const uint32_t qm = __reduce_max_sync(0xffffffffu, __float_as_uint(qv));
        const uint32_t km = __reduce_max_sync(0xffffffffu, __float_as_uint(kv));
        safe = (__uint_as_float(qm) * __uint_as_float(km) * (16.f * 1.05f) < AT_SAFE2);
    }
    const uint64_t dK0 = mk_desc(DESC_SW32, sK, 16, 256);
    const uint64_t dC = mk_desc(DESC_SW32, sb + AT_CT, 16, 0);
    const uint64_t dV0 = mk_desc(DESC_SW32, sV, AT_ONES - AT_V, 256);
    constexpr int64_t VSTEP = 32 - (32 << 16);
    const uint32_t lane4 = lane * 4;
    uint32_t aone[4];
    asm volatile("ld.shared.v4.u32 {%0,%1,%2,%3}, [%4];" : "=r"(aone[0]), "=r"(aone[1]), "=r"(aone[2]), "=r"(aone[3]) : "r"(sb + AT_CT + 256 + ((lane & 3) == 0 ? 0 : 16)));
    const int g = lane >> 2, t = lane & 3;
    constexpr int NT = AT_NT, NP = AT_NP;
    const int oBranch = blockIdx.x >> 6, oNt = blockIdx.x & 3;

#pragma unroll 1
    for (int qi = 0; qi < 2; qi++) {
        const int qt = wg * 2 + qi;
        const int row0 = qb * 512 + qt * 64 + warp * 16;
        uint32_t qa[4];
        ldsm_x4(sQ + (qt * 64 + warp * 16 + (lane & 7) + ((lane >> 3) & 1) * 8) * 32 + ((((lane >> 4) ^ ((lane & 7) >> 2))) << 4), qa);
        float o[12], s[NT / 2];
#pragma unroll
        for (int i = 0; i < 12; i++) o[i] = 0.f;
#pragma unroll
        for (int i = 0; i < NT / 2; i++) s[i] = 0.f;
        fence_regs(o); fence_regs(s);
        if (safe) {
            uint32_t pa[NT / 4], pb[NT / 4];
            auto issue_qk = [&](uint64_t dK, int np) {
                wgmma_rs_n64<0>(s, qa, dK);
                if (np == 24) wgmma_rs_n24<1>(s, aone, dC); else if (np == 32) wgmma_rs_n32<1>(s, aone, dC); else wgmma_rs_n40<1>(s, aone, dC);
            };
            mbar_wait(sBar, 0);
            wg_fence();
            issue_qk(dK0, NP);
            wg_commit();
            wg_wait<0>();
            fence_regs(s);
            att_exp<NT, NP>(s, pa, lane4);
            if (qi == 0 && wg == 2 && wwarp == 0) {
                asm volatile("{.reg .pred p;\nelect.sync _|p, 0xffffffff;\n@p red.release.gpu.global.add.s32 [%0], 1;\n}" ::"l"(&g_cnt.qkvA[blockIdx.x & 7]) : "memory");
            }
            uint64_t dK = dK0, dV = dV0;
            auto step = [&](uint32_t (&pc)[NT / 4], uint32_t (&pn)[NT / 4], bool last, int jt) {
                wg_fence();
                if (!last) { issue_qk(dK + (uint64_t)(jt * NT * 2 + NT * 2), (jt & 1) ? NP : AT_NP2); wg_commit(); }
#pragma unroll
                for (int kk = 0; kk < NT / 16; kk++) wgmma_rs_n24_tb<1>(o, pc + kk * 4, dV + (uint64_t)((int64_t)(jt * (NT / 16) + kk) * VSTEP));
                wg_commit();
                if (!last) {
                    wg_wait<1>();
                    fence_regs(s);
                    if (jt & 1) att_exp<NT, NP>(s, pn, lane4); else att_exp<NT, AT_NP2>(s, pn, lane4);
                }
                if (last || jt == 3) { wg_wait<0>(); fence_regs(pc); fence_regs(o); }
            };
            constexpr int TPC = 256 / NT;
#pragma unroll 1
            for (int cch = 0; cch < NCH; cch++) {
#pragma unroll
                for (int jj = 0; jj < TPC; jj += 2) {
                    step(pa, pb, false, jj);
                    if (jj + 2 == TPC) {
                        if (cch == NCH - 1) break;
                        mbar_wait(sBar + 8 * (cch + 1), 0);
                    }
                    step(pb, pa, false, jj + 1);
                }
                dK += 256 * 2; dV += (uint64_t)(16 * VSTEP);
                if (qi == 1 && wwarp == 0 && cch < NCH - 1) {
                    mbar_arrive_elect(sb + B_CONS + 8 * cch);
                    if (cch >= 1 && wg == ((cch - 1) & 3)) { mbar_wait(sb + B_CONS + 8 * (cch - 1), 0); load_wo_elect(mp, oBranch, oNt, cch - 1); }
                }
            }
            dV -= (uint64_t)(16 * VSTEP);
            step(pb, pa, true, TPC - 1);
            if (qi == 1 && wwarp == 0) {
                mbar_arrive_elect(sb + B_CONS + 8 * 7);
                if (wg == 2) { mbar_wait(sb + B_CONS + 8 * 6, 0); load_wo_elect(mp, oBranch, oNt, 6); }
                if (wg == 3) { mbar_wait(sb + B_CONS + 8 * 7, 0); load_wo_elect(mp, oBranch, oNt, 7); }
            }
        } else {
            if (qi == 0 && tid == 256) signal_add(&g_cnt.qkvA[blockIdx.x & 7]);
            float m0 = -INFINITY, m1 = -INFINITY;
            uint32_t p[NT / 4];
#pragma unroll 1
            for (int j = 0; j < S_LEN / NT; j++) {
                if ((j * NT) % 256 == 0) mbar_wait(sBar + 8 * ((j * NT) / 256), 0);
                wg_fence();
                wgmma_rs_n64<0>(s, qa, dK0 + (uint64_t)(j * NT * 2));
                wg_commit();
                wg_wait<0>();
                fence_regs(s); fence_regs(o);
                float t0 = m0, t1 = m1;
#pragma unroll
                for (int i = 0; i < NT / 2; i += 4) { t0 = fmaxf(t0, fmaxf(s[i], s[i + 1])); t1 = fmaxf(t1, fmaxf(s[i + 2], s[i + 3])); }
                t0 = fmaxf(t0, __shfl_xor_sync(0xffffffffu, t0, 1)); t0 = fmaxf(t0, __shfl_xor_sync(0xffffffffu, t0, 2));
                t1 = fmaxf(t1, __shfl_xor_sync(0xffffffffu, t1, 1)); t1 = fmaxf(t1, __shfl_xor_sync(0xffffffffu, t1, 2));
                const float r0 = ex2f(m0 - t0), r1 = ex2f(m1 - t1);
                m0 = t0; m1 = t1;
#pragma unroll
                for (int i = 0; i < 12; i += 4) { o[i] *= r0; o[i + 1] *= r0; o[i + 2] *= r1; o[i + 3] *= r1; }
#pragma unroll
                for (int i = 0; i < NT / 4; i += 2) {
                    p[i] = pack_bf16(ex2f(s[2 * i] - m0), ex2f(s[2 * i + 1] - m0));
                    p[i + 1] = pack_bf16(ex2f(s[2 * i + 2] - m1), ex2f(s[2 * i + 3] - m1));
                }
                fence_regs(o);
                wg_fence();
#pragma unroll
                for (int kk = 0; kk < NT / 16; kk++) wgmma_rs_n24_tb<1>(o, p + kk * 4, dV0 + (uint64_t)((int64_t)(j * (NT / 16) + kk) * VSTEP));
                wg_commit();
                wg_wait<0>();
                fence_regs(p);
            }
            fence_regs(o);
        }
        const float l0 = 1.f / o[8], l1 = 1.f / o[10];
        uint32_t* op0 = (uint32_t*)(g_o + (size_t)(row0 + g) * 1024 + 512 + h * 16);
        uint32_t* op1 = (uint32_t*)(g_o + (size_t)(row0 + g + 8) * 1024 + 512 + h * 16);
        op0[t] = pack_bf16(o[0] * l0, o[1] * l0);
        op0[4 + t] = pack_bf16(o[4] * l0, o[5] * l0);
        op1[t] = pack_bf16(o[2] * l1, o[3] * l1);
        op1[4 + t] = pack_bf16(o[6] * l1, o[7] * l1);
    }
    named_bar(4 + wg, 128);
    if ((tid & 127) == 0) signal_add(&g_cnt.oB[(qb * 4 + wg) * 8 + (h >> 2)]);
    __syncthreads();
    if (!safe && tid == 0) {
        for (int c = 0; c < 8; c++) load_wo(mp, oBranch, oNt, c);
    }
}

__device__ __forceinline__ void phase_out(uint8_t* smem, const Maps& mp) {
    (void)smem;
    constexpr uint32_t sb = SM_BASE;
    const int tid = threadIdx.x, warp = tid >> 5, lane = tid & 31;
    const int branchB = blockIdx.x >> 6;
    const int mt = (blockIdx.x & 63) >> 2, nt = blockIdx.x & 3;
    const int wg = __shfl_sync(0xffffffffu, warp >> 2, 0);
    if (wg == 2) {
        if (tid < 256 + 32) {
            if (lane == 0) { tma_prefetch_desc(&mp.o); tma_prefetch_desc(&mp.out); }
            const int* cnt = branchB ? &g_cnt.oB[mt * 8 + (lane & 7)] : &g_cnt.oA;
            int next = 0, spins = 0;
            while (next < 8) {
                int v;
                asm volatile("ld.acquire.gpu.global.s32 %0, [%1];" : "=r"(v) : "l"(cnt) : "memory");
                const uint32_t ready = __ballot_sync(0xffffffffu, v >= 4);
                __syncwarp();
                if (lane == 0) {
                    fence_async_all();
                    for (int kb = next; kb < 8 && ((ready >> kb) & 1); kb++) {
                        const int s = kb & 3;
                        if (kb >= 4) mbar_wait(sb + B_OEMPTY + 8 * s, 0);
                        mbar_expect_tx(sb + B_OFULL + 8 * s, 16384);
                        tma_load_2d(sb + P3_O + s * 16384, &mp.o, branchB * 512 + kb * 64, mt * 128, sb + B_OFULL + 8 * s);
                    }
                }
                while (next < 8 && ((ready >> next) & 1)) next++;
                __syncwarp();
                if (++spins > (1 << 22)) __trap();
                if (next < 8) __nanosleep(SPIN_NS);
            }
            if (lane == 0) finish_ticket();
        }
        return;
    }
    if (wg == 3) return;
    float acc[64];
#pragma unroll
    for (int i = 0; i < 64; i++) acc[i] = 0.f;
    fence_regs(acc);
    const uint64_t dA0 = mk_desc(DESC_SW128, sb + P3_O + wg * 8192, 16, 1024);
#pragma unroll
    for (int kb = 0; kb < 8; kb++) {
        const int s = kb & 3;
        mbar_wait(sb + B_WFULL + 8 * kb, 0);
        mbar_wait(sb + B_OFULL + 8 * s, kb >> 2);
        const uint64_t dA = dA0 + (uint64_t)(s * (16384 >> 4));
        const uint64_t dB = mk_desc(DESC_SW128, sb + AT_K + kb * 8192, AT_V - AT_K, 1024);
        wg_fence();
#pragma unroll
        for (int k = 0; k < 4; k++) wgmma_ss_n128_tb(acc, dA + k * 2, dB + k * 128, 1);
        wg_commit();
        if (kb >= 1 && kb <= 4) {
            wg_wait<1>();
            if ((tid & 127) == 0) mbar_arrive(sb + B_OEMPTY + 8 * (kb - 1));
        }
    }
    wg_wait<0>();
    fence_regs(acc);
    const int wq = warp & 3;
    const uint32_t stg = sb + P3_O + wg * 8192;
    const int lr = wq * 16 + (lane & 7) + ((lane >> 3) & 1) * 8, lc = lane >> 4;
#pragma unroll
    for (int j = 0; j < 8; j++) {
        const float* a = acc + j * 8;
        const int chunk = (j & 3) * 2 + lc;
        stsm_x4(stg + (j >> 2) * 16384 + lr * 128 + ((chunk ^ (lr & 7)) << 4),
                pack_bf16(a[0], a[1]), pack_bf16(a[2], a[3]), pack_bf16(a[4], a[5]), pack_bf16(a[6], a[7]));
    }
    fence_async_smem();
    named_bar(4 + wg, 128);
    if ((tid & 127) < 2) {
        const int j = tid & 1;
        tma_store_2d(&mp.out, stg + j * 16384, branchB * 512 + nt * 128 + j * 64, mt * 128 + wg * 64);
        bulk_commit();
        asm volatile("cp.async.bulk.wait_group.read 0;" ::: "memory");
    }
}

__device__ __noinline__ void linattn_mid(uint8_t* smem, int cta, const CUtensorMap* tmO16) {
    constexpr uint32_t sb = SM_BASE;
    const int tid = threadIdx.x, warp = tid >> 5, lane = tid & 31;
    constexpr int NBUF = 4;
    const uint32_t sBar = sb;
    const uint32_t sQ0 = sb + 1024;
    const uint32_t sSt = sQ0 + NBUF * 32768;
    float* skv = (float*)(smem + 1024 + NBUF * 32768 + 65536);
    if (tid == 0) { for (int i = 0; i < NBUF; i++) { mbar_init(sBar + 8 * i, 1); mbar_init(sBar + 64 + 8 * i, 16); } fence_mbar_init(); }
    __syncthreads();
    if (warp == 0 && lane == 0) { spin_ge(&g_cnt.qkvA[2 * cta], 16); spin_ge(&g_cnt.qkvA[2 * cta + 1], 16); }
    __syncthreads();
    if (lane == 0) fence_async_all();
    __syncwarp();
    auto load_chunk = [&](int c, int j) {
        bulk_g2s(sQ0 + (c % NBUF) * 32768 + j * 8192, g_qA + ((size_t)(cta * 8 + (c >> 3) * 4 + j) * S_LEN + (c & 7) * 256) * 16, 8192, sBar + 8 * (c % NBUF));
    };
    if (lane == 0 && warp < NBUF) {
        mbar_expect_tx(sBar + 8 * warp, 32768);
        for (int j = 0; j < 4; j++) load_chunk(warp, j);
    }
    {
        const int hh = tid >> 6, e = tid & 63;
        const float* gp = g_kvp + (size_t)(cta * 8 + hh) * 272 + e * 4;
        const float* gz = g_kvp + (size_t)(cta * 8 + ((tid >> 4) & 7)) * 272 + 256 + (tid & 15);
        float4 v0, v1, v2, v3, v4, v5, v6, v7;
        float z[16];
#define LD4(m) (*(const float4*)(gp + (size_t)(m) * NH * 272))
#define ADD4(a, b) (a).x += (b).x, (a).y += (b).y, (a).z += (b).z, (a).w += (b).w
        if (tid < 128) {
#pragma unroll
            for (int m = 0; m < 16; m++) z[m] = gz[(size_t)m * NH * 272];
        }
        v0 = LD4(0); v1 = LD4(1); v2 = LD4(2); v3 = LD4(3); v4 = LD4(4); v5 = LD4(5); v6 = LD4(6); v7 = LD4(7);
        {
            const float4 w0 = LD4(8), w1 = LD4(9), w2 = LD4(10), w3 = LD4(11), w4 = LD4(12), w5 = LD4(13), w6 = LD4(14), w7 = LD4(15);
            ADD4(v0, w0); ADD4(v1, w1); ADD4(v2, w2); ADD4(v3, w3); ADD4(v4, w4); ADD4(v5, w5); ADD4(v6, w6); ADD4(v7, w7);
        }
        ADD4(v0, v4); ADD4(v1, v5); ADD4(v2, v6); ADD4(v3, v7); ADD4(v0, v2); ADD4(v1, v3); ADD4(v0, v1);
#undef LD4
#undef ADD4
        *(float4*)(skv + hh * 272 + e * 4) = v0;
        if (tid < 128) {
#pragma unroll
            for (int w = 8; w > 0; w >>= 1) {
#pragma unroll
                for (int m = 0; m < w; m++) z[m] += z[m + w];
            }
            skv[((tid >> 4) & 7) * 272 + 256 + (tid & 15)] = z[0];
        }
    }
    __syncthreads();
    if (tid == 511) finish_ticket();
    const int g = lane >> 2, t = lane & 3;
    const int lr = (lane & 7) + ((lane >> 3) & 1) * 8, lc = lane >> 4;
    const uint32_t loff = (warp * 16 + lr) * 32 + ((lc ^ ((lr & 7) >> 2)) << 4);
#pragma unroll 1
    for (int quad = 0; quad < 2; quad++) {
        uint32_t bf[4][6];
#pragma unroll
        for (int j = 0; j < 4; j++) {
            const float* kv = skv + (quad * 4 + j) * 272;
            bf[j][0] = pack_bf16(kv[(2 * t) * 16 + g], kv[(2 * t + 1) * 16 + g]);
            bf[j][1] = pack_bf16(kv[(2 * t + 8) * 16 + g], kv[(2 * t + 9) * 16 + g]);
            bf[j][2] = pack_bf16(kv[(2 * t) * 16 + 8 + g], kv[(2 * t + 1) * 16 + 8 + g]);
            bf[j][3] = pack_bf16(kv[(2 * t + 8) * 16 + 8 + g], kv[(2 * t + 9) * 16 + 8 + g]);
            bf[j][4] = pack_bf16(kv[256 + 2 * t], kv[256 + 2 * t + 1]);
            bf[j][5] = pack_bf16(kv[256 + 2 * t + 8], kv[256 + 2 * t + 9]);
        }
#pragma unroll 1
        for (int rc = 0; rc < 8; rc++) {
            const int c = quad * 8 + rc;
            mbar_wait(sBar + 8 * (c % NBUF), (c / NBUF) & 1);
            const uint32_t qb = sQ0 + (c % NBUF) * 32768 + loff;
            const uint32_t stg = sSt + (c & 1) * 32768 + warp * 2048;
            uint32_t a[4][4];
#pragma unroll
            for (int j = 0; j < 4; j++) ldsm_x4(qb + j * 8192, a[j]);
            __syncwarp();
            if (lane == 0) {
                mbar_arrive(sBar + 64 + 8 * (c % NBUF));
                if (c >= 1 && warp == (c & 15) && c - 1 + NBUF < 16) {
                    const int cp = c - 1;
                    mbar_wait(sBar + 64 + 8 * (cp % NBUF), (cp / NBUF) & 1);
                    mbar_expect_tx(sBar + 8 * (cp % NBUF), 32768);
                    for (int j = 0; j < 4; j++) load_chunk(cp + NBUF, j);
                }
                if (c >= 2) asm volatile("cp.async.bulk.wait_group.read 1;" ::: "memory");
            }
            __syncwarp();
#pragma unroll
            for (int j = 0; j < 4; j++) {
#pragma unroll
                for (int i = 0; i < 4; i++) a[j][i] = phi_bf16x2(a[j][i]);
                float n0[4] = {0.f, 0.f, 0.f, 0.f}, n1[4] = {0.f, 0.f, 0.f, 0.f}, dn[4] = {0.f, 0.f, 0.f, 0.f};
                mma_bf16(n0, a[j], bf[j][0], bf[j][1]);
                mma_bf16(n1, a[j], bf[j][2], bf[j][3]);
                mma_bf16(dn, a[j], bf[j][4], bf[j][5]);
                const float i0 = rcp_fast(dn[0] + 1e-6f), i1 = rcp_fast(dn[2] + 1e-6f);
                stsm_x4(stg + lr * 128 + (((j * 2 + lc) ^ (lr & 7)) << 4),
                        pack_bf16(n0[0] * i0, n0[1] * i0), pack_bf16(n0[2] * i1, n0[3] * i1),
                        pack_bf16(n1[0] * i0, n1[1] * i0), pack_bf16(n1[2] * i1, n1[3] * i1));
            }
            fence_async_smem();
            __syncwarp();
            if (lane == 0) {
                tma_store_2d(tmO16, stg, cta * 128 + quad * 64, rc * 256 + warp * 16);
                bulk_commit();
            }
        }
    }
    if (lane == 0) { bulk_wait0(); fence_async_all(); }
    __syncthreads();
    if (tid == 0) signal_add(&g_cnt.oA);
}

__global__ void __launch_bounds__(512, 1) fused_kernel(const __grid_constant__ Maps mp) {
    extern __shared__ __align__(1024) uint8_t smem[];
    if (smem_u32(smem) != SM_BASE) __trap();
    if (blockIdx.x >= 128) {
        linattn_mid(smem, blockIdx.x - 128, &mp.o16);
    } else {
        phase_qkv(smem, mp);
        phase_attn(smem, mp);
        phase_out(smem, mp);
    }
}

typedef CUresult (*EncodeFn)(CUtensorMap*, CUtensorMapDataType, cuuint32_t, void*, const cuuint64_t*, const cuuint64_t*,
                             const cuuint32_t*, const cuuint32_t*, CUtensorMapInterleave, CUtensorMapSwizzle,
                             CUtensorMapL2promotion, CUtensorMapFloatOOBfill);

void make_map(EncodeFn enc, CUtensorMap* tm, const void* ptr, uint64_t cols, uint64_t rows, uint32_t boxc, uint32_t boxr) {
    cuuint64_t dims[2] = {cols, rows};
    cuuint64_t strides[1] = {cols * 2};
    cuuint32_t box[2] = {boxc, boxr};
    cuuint32_t es[2] = {1, 1};
    enc(tm, CU_TENSOR_MAP_DATA_TYPE_BFLOAT16, 2, const_cast<void*>(ptr), dims, strides, box, es, CU_TENSOR_MAP_INTERLEAVE_NONE,
        CU_TENSOR_MAP_SWIZZLE_128B, CU_TENSOR_MAP_L2_PROMOTION_L2_256B, CU_TENSOR_MAP_FLOAT_OOB_FILL_NONE);
}

struct HostState {
    bool init;
    const void* key[7];
    Maps mp;
};
HostState g_hs;

}

extern "C" void kernel_launch(void* const* d_in, const int* in_sizes, int n_in, void* d_out, int out_size) {
    (void)in_sizes; (void)n_in; (void)out_size;
    HostState& hs = g_hs;
    bool same = hs.init && hs.key[6] == d_out;
    for (int i = 0; i < 6 && same; i++) same = hs.key[i] == d_in[i];
    if (!same) {
        void* fn = nullptr;
        cudaDriverEntryPointQueryResult qr;
        cudaGetDriverEntryPoint("cuTensorMapEncodeTiled", &fn, cudaEnableDefault, &qr);
        EncodeFn enc = (EncodeFn)fn;
        void* po = nullptr;
        cudaGetSymbolAddress(&po, g_o);
        make_map(enc, &hs.mp.xA, d_in[0], 512, 2048, 64, 128);
        make_map(enc, &hs.mp.wA, d_in[1], 1536, 512, 64, 64);
        make_map(enc, &hs.mp.woA, d_in[2], 512, 512, 64, 64);
        make_map(enc, &hs.mp.xB, d_in[3], 512, 2048, 64, 128);
        make_map(enc, &hs.mp.wB, d_in[4], 1536, 512, 64, 64);
        make_map(enc, &hs.mp.woB, d_in[5], 512, 512, 64, 64);
        make_map(enc, &hs.mp.o, po, 1024, 2048, 64, 128);
        make_map(enc, &hs.mp.o16, po, 1024, 2048, 64, 16);
        make_map(enc, &hs.mp.out, d_out, 1024, 2048, 64, 64);
        cudaFuncSetAttribute(fused_kernel, cudaFuncAttributeMaxDynamicSharedMemorySize, SMEM_BYTES);
        for (int i = 0; i < 6; i++) hs.key[i] = d_in[i];
        hs.key[6] = d_out;
        hs.init = true;
    }
    fused_kernel<<<132, 512, SMEM_BYTES, cudaStreamPerThread>>>(hs.mp);
}
```

```cpp
#include <cuda_runtime.h>
#include <cuda_bf16.h>
#include <cuda.h>
#include <stdint.h>

namespace {

constexpr int S_LEN = 2048;
constexpr int NH = 32;

__device__ __align__(1024) uint16_t g_qB[NH * S_LEN * 16];
__device__ __align__(1024) uint16_t g_kB[NH * S_LEN * 16];
__device__ __align__(1024) uint16_t g_vB[NH * S_LEN * 16];
__device__ __align__(1024) uint16_t g_qA[NH * S_LEN * 16];
__device__ __align__(1024) uint16_t g_o[S_LEN * 1024];
__device__ __align__(16) float g_kvp[16 * NH * 272];
__device__ __align__(64) float g_qn[NH * 16];
__device__ __align__(64) float g_kn[NH * 16];

struct Counters {
    int qkvB[8];
    int qkvA[8];
    int oB[16 * 8];
    int oA;
    int done;
};
__device__ Counters g_cnt;

__device__ __forceinline__ uint32_t smem_u32(const void* p) { return (uint32_t)__cvta_generic_to_shared(p); }
__device__ __forceinline__ void wg_fence() { asm volatile("wgmma.fence.sync.aligned;" ::: "memory"); }
__device__ __forceinline__ void wg_commit() { asm volatile("wgmma.commit_group.sync.aligned;" ::: "memory"); }
template <int N> __device__ __forceinline__ void wg_wait() { asm volatile("wgmma.wait_group.sync.aligned %0;" ::"n"(N) : "memory"); }
__device__ __forceinline__ void mbar_init(uint32_t bar, uint32_t cnt) { asm volatile("mbarrier.init.shared::cta.b64 [%0], %1;" ::"r"(bar), "r"(cnt)); }
__device__ __forceinline__ void mbar_expect_tx(uint32_t bar, uint32_t bytes) {
    asm volatile("mbarrier.arrive.expect_tx.shared::cta.b64 _, [%0], %1;" ::"r"(bar), "r"(bytes) : "memory");
}
__device__ __forceinline__ void mbar_wait(uint32_t bar, uint32_t parity) {
    asm volatile(
        "{.reg .pred p;\n"
        "WAIT_LOOP:\n"
        "mbarrier.try_wait.parity.shared::cta.b64 p, [%0], %1;\n"
        "@p bra WAIT_DONE;\n"
        "bra WAIT_LOOP;\n"
        "WAIT_DONE:\n}" ::"r"(bar), "r"(parity) : "memory");
}
__device__ __forceinline__ void mbar_arrive(uint32_t bar) { asm volatile("mbarrier.arrive.shared::cta.b64 _, [%0];" ::"r"(bar) : "memory"); }
__device__ __forceinline__ void fence_mbar_init() { asm volatile("fence.mbarrier_init.release.cluster;" ::: "memory"); }
__device__ __forceinline__ void fence_async_smem() { asm volatile("fence.proxy.async.shared::cta;" ::: "memory"); }
constexpr int SPIN_NS = 100;
__device__ __forceinline__ void spin_ge(const int* p, int target) {
    int it = 0;
    while (true) {
        int v;
        asm volatile("ld.acquire.gpu.global.s32 %0, [%1];" : "=r"(v) : "l"(p) : "memory");
        if (v >= target) break;
        if (++it > (1 << 22)) __trap();
        __nanosleep(SPIN_NS);
    }
}
__device__ __forceinline__ void finish_ticket() {
    if (atomicAdd(&g_cnt.done, 1) == (int)gridDim.x - 1) {
        int* c = (int*)&g_cnt;
        for (int i = 0; i < (int)(sizeof(Counters) / sizeof(int)); i++) c[i] = 0;
    }
}
__device__ __forceinline__ void signal_add(int* p) { asm volatile("red.release.gpu.global.add.s32 [%0], 1;" ::"l"(p) : "memory"); }
__device__ __forceinline__ void fence_async_all() { asm volatile("fence.proxy.async.global;" ::: "memory"); }
__device__ __forceinline__ void named_bar(int id, int n) { asm volatile("bar.sync %0, %1;" ::"r"(id), "r"(n) : "memory"); }

__device__ __forceinline__ void bulk_g2s(uint32_t dst, const void* src, uint32_t bytes, uint32_t bar) {
    asm volatile("cp.async.bulk.shared::cluster.global.mbarrier::complete_tx::bytes [%0], [%1], %2, [%3];" ::"r"(dst), "l"(src), "r"(bytes), "r"(bar) : "memory");
}
__device__ __forceinline__ void bulk_commit() { asm volatile("cp.async.bulk.commit_group;" ::: "memory"); }
__device__ __forceinline__ void bulk_wait0() { asm volatile("cp.async.bulk.wait_group 0;" ::: "memory"); }
__device__ __forceinline__ void tma_load_2d(uint32_t dst, const CUtensorMap* tm, int c0, int c1, uint32_t bar) {
    asm volatile("cp.async.bulk.tensor.2d.shared::cluster.global.mbarrier::complete_tx::bytes [%0], [%1, {%3, %4}], [%2];" ::"r"(dst), "l"(tm), "r"(bar), "r"(c0), "r"(c1) : "memory");
}
__device__ __forceinline__ void tma_store_2d(const CUtensorMap* tm, uint32_t src, int c0, int c1) {
    asm volatile("cp.async.bulk.tensor.2d.global.shared::cta.bulk_group [%0, {%2, %3}], [%1];" ::"l"(tm), "r"(src), "r"(c0), "r"(c1) : "memory");
}
__device__ __forceinline__ void tma_prefetch_desc(const CUtensorMap* tm) { asm volatile("prefetch.tensormap [%0];" ::"l"(tm) : "memory"); }

__device__ __forceinline__ uint32_t pack_bf16(float lo, float hi) {
    uint32_t r; asm("cvt.rn.bf16x2.f32 %0, %1, %2;" : "=r"(r) : "f"(hi), "f"(lo)); return r;
}
__device__ __forceinline__ float ex2f(float x) { float r; asm("ex2.approx.ftz.f32 %0, %1;" : "=f"(r) : "f"(x)); return r; }
__device__ __forceinline__ float bf_lo(uint32_t p) { return __uint_as_float(p << 16); }
__device__ __forceinline__ float bf_hi(uint32_t p) { return __uint_as_float(p & 0xFFFF0000u); }
__device__ __forceinline__ void stsm_x4(uint32_t addr, uint32_t r0, uint32_t r1, uint32_t r2, uint32_t r3) {
    asm volatile("stmatrix.sync.aligned.m8n8.x4.shared.b16 [%0], {%1,%2,%3,%4};" ::"r"(addr), "r"(r0), "r"(r1), "r"(r2), "r"(r3) : "memory");
}
__device__ __forceinline__ void ldsm_x4(uint32_t addr, uint32_t* r) {
    asm volatile("ldmatrix.sync.aligned.m8n8.x4.shared.b16 {%0,%1,%2,%3}, [%4];" : "=r"(r[0]), "=r"(r[1]), "=r"(r[2]), "=r"(r[3]) : "r"(addr) : "memory");
}
__device__ __forceinline__ void ldsm_x4_t(uint32_t addr, uint32_t* r) {
    asm volatile("ldmatrix.sync.aligned.m8n8.x4.trans.shared.b16 {%0,%1,%2,%3}, [%4];" : "=r"(r[0]), "=r"(r[1]), "=r"(r[2]), "=r"(r[3]) : "r"(addr) : "memory");
}
__device__ __forceinline__ void mma_bf16(float* d, const uint32_t* a, uint32_t b0, uint32_t b1) {
    asm volatile("mma.sync.aligned.m16n8k16.row.col.f32.bf16.bf16.f32 {%0,%1,%2,%3}, {%4,%5,%6,%7}, {%8,%9}, {%0,%1,%2,%3};"
                 : "+f"(d[0]), "+f"(d[1]), "+f"(d[2]), "+f"(d[3]) : "r"(a[0]), "r"(a[1]), "r"(a[2]), "r"(a[3]), "r"(b0), "r"(b1));
}
__device__ __forceinline__ uint32_t phi_bf16x2(uint32_t p) {
    const float t0 = bf_lo(p), t1 = bf_hi(p);
    const float a0 = fmaf(t0 + fabsf(t0), 0.5f, ex2f((t0 - fabsf(t0)) * 0.7213475204444817f));
    const float a1 = fmaf(t1 + fabsf(t1), 0.5f, ex2f((t1 - fabsf(t1)) * 0.7213475204444817f));
    const uint32_t a = pack_bf16(a0, a1);
    uint32_t r;
    asm("add.rn.bf16x2 %0, %1, %2;" : "=r"(r) : "r"(a), "r"(0x35863586u));
    return r;
}
__device__ __forceinline__ float rcp_fast(float x) { float r; asm("rcp.approx.ftz.f32 %0, %1;" : "=f"(r) : "f"(x)); return r; }
template <typename T, int N> __device__ __forceinline__ void fence_regs(T (&r)[N]) {
#pragma unroll
    for (int i = 0; i < N; i++) {
        if constexpr (sizeof(T) == 4 && T(0.5) != T(0)) asm volatile("" : "+f"(r[i])::"memory");
        else asm volatile("" : "+r"(r[i])::"memory");
    }
}

__device__ __forceinline__ void wgmma_ss_n192_tb(float* d, uint64_t da, uint64_t db, int sd) {
  asm volatile("{.reg .pred p; setp.ne.b32 p, %98, 0; wgmma.mma_async.sync.aligned.m64n192k16.f32.bf16.bf16 {%0,%1,%2,%3,%4,%5,%6,%7,%8,%9,%10,%11,%12,%13,%14,%15,%16,%17,%18,%19,%20,%21,%22,%23,%24,%25,%26,%27,%28,%29,%30,%31,%32,%33,%34,%35,%36,%37,%38,%39,%40,%41,%42,%43,%44,%45,%46,%47,%48,%49,%50,%51,%52,%53,%54,%55,%56,%57,%58,%59,%60,%61,%62,%63,%64,%65,%66,%67,%68,%69,%70,%71,%72,%73,%74,%75,%76,%77,%78,%79,%80,%81,%82,%83,%84,%85,%86,%87,%88,%89,%90,%91,%92,%93,%94,%95}, %96, %97, p, 1, 1, 0, 1;}"
    : "+f"(d[0]), "+f"(d[1]), "+f"(d[2]), "+f"(d[3]), "+f"(d[4]), "+f"(d[5]), "+f"(d[6]), "+f"(d[7]), "+f"(d[8]), "+f"(d[9]), "+f"(d[10]), "+f"(d[11]), "+f"(d[12]), "+f"(d[13]), "+f"(d[14]), "+f"(d[15]), "+f"(d[16]), "+f"(d[17]), "+f"(d[18]), "+f"(d[19]), "+f"(d[20]), "+f"(d[21]), "+f"(d[22]), "+f"(d[23]), "+f"(d[24]), "+f"(d[25]), "+f"(d[26]), "+f"(d[27]), "+f"(d[28]), "+f"(d[29]), "+f"(d[30]), "+f"(d[31]), "+f"(d[32]), "+f"(d[33]), "+f"(d[34]), "+f"(d[35]), "+f"(d[36]), "+f"(d[37]), "+f"(d[38]), "+f"(d[39]), "+f"(d[40]), "+f"(d[41]), "+f"(d[42]), "+f"(d[43]), "+f"(d[44]), "+f"(d[45]), "+f"(d[46]), "+f"(d[47]), "+f"(d[48]), "+f"(d[49]), "+f"(d[50]), "+f"(d[51]), "+f"(d[52]), "+f"(d[53]), "+f"(d[54]), "+f"(d[55]), "+f"(d[56]), "+f"(d[57]), "+f"(d[58]), "+f"(d[59]), "+f"(d[60]), "+f"(d[61]), "+f"(d[62]), "+f"(d[63]), "+f"(d[64]), "+f"(d[65]), "+f"(d[66]), "+f"(d[67]), "+f"(d[68]), "+f"(d[69]), "+f"(d[70]), "+f"(d[71]), "+f"(d[72]), "+f"(d[73]), "+f"(d[74]), "+f"(d[75]), "+f"(d[76]), "+f"(d[77]), "+f"(d[78]), "+f"(d[79]), "+f"(d[80]), "+f"(d[81]), "+f"(d[82]), "+f"(d[83]), "+f"(d[84]), "+f"(d[85]), "+f"(d[86]), "+f"(d[87]), "+f"(d[88]), "+f"(d[89]), "+f"(d[90]), "+f"(d[91]), "+f"(d[92]), "+f"(d[93]), "+f"(d[94]), "+f"(d[95]) : "l"(da), "l"(db), "r"(sd));
}
__device__ __forceinline__ void wgmma_ss_n128_tb(float* d, uint64_t da, uint64_t db, int sd) {
  asm volatile("{.reg .pred p; setp.ne.b32 p, %66, 0; wgmma.mma_async.sync.aligned.m64n128k16.f32.bf16.bf16 {%0,%1,%2,%3,%4,%5,%6,%7,%8,%9,%10,%11,%12,%13,%14,%15,%16,%17,%18,%19,%20,%21,%22,%23,%24,%25,%26,%27,%28,%29,%30,%31,%32,%33,%34,%35,%36,%37,%38,%39,%40,%41,%42,%43,%44,%45,%46,%47,%48,%49,%50,%51,%52,%53,%54,%55,%56,%57,%58,%59,%60,%61,%62,%63}, %64, %65, p, 1, 1, 0, 1;}"
    : "+f"(d[0]), "+f"(d[1]), "+f"(d[2]), "+f"(d[3]), "+f"(d[4]), "+f"(d[5]), "+f"(d[6]), "+f"(d[7]), "+f"(d[8]), "+f"(d[9]), "+f"(d[10]), "+f"(d[11]), "+f"(d[12]), "+f"(d[13]), "+f"(d[14]), "+f"(d[15]), "+f"(d[16]), "+f"(d[17]), "+f"(d[18]), "+f"(d[19]), "+f"(d[20]), "+f"(d[21]), "+f"(d[22]), "+f"(d[23]), "+f"(d[24]), "+f"(d[25]), "+f"(d[26]), "+f"(d[27]), "+f"(d[28]), "+f"(d[29]), "+f"(d[30]), "+f"(d[31]), "+f"(d[32]), "+f"(d[33]), "+f"(d[34]), "+f"(d[35]), "+f"(d[36]), "+f"(d[37]), "+f"(d[38]), "+f"(d[39]), "+f"(d[40]), "+f"(d[41]), "+f"(d[42]), "+f"(d[43]), "+f"(d[44]), "+f"(d[45]), "+f"(d[46]), "+f"(d[47]), "+f"(d[48]), "+f"(d[49]), "+f"(d[50]), "+f"(d[51]), "+f"(d[52]), "+f"(d[53]), "+f"(d[54]), "+f"(d[55]), "+f"(d[56]), "+f"(d[57]), "+f"(d[58]), "+f"(d[59]), "+f"(d[60]), "+f"(d[61]), "+f"(d[62]), "+f"(d[63]) : "l"(da), "l"(db), "r"(sd));
}
template<int SD> __device__ __forceinline__ void wgmma_rs_n64(float* d, const uint32_t* a, uint64_t db) {
  asm volatile("{.reg .pred p; setp.ne.b32 p, %37, 0; wgmma.mma_async.sync.aligned.m64n64k16.f32.bf16.bf16 {%0,%1,%2,%3,%4,%5,%6,%7,%8,%9,%10,%11,%12,%13,%14,%15,%16,%17,%18,%19,%20,%21,%22,%23,%24,%25,%26,%27,%28,%29,%30,%31}, {%32,%33,%34,%35}, %36, p, 1, 1, 0;}"
    : "+f"(d[0]), "+f"(d[1]), "+f"(d[2]), "+f"(d[3]), "+f"(d[4]), "+f"(d[5]), "+f"(d[6]), "+f"(d[7]), "+f"(d[8]), "+f"(d[9]), "+f"(d[10]), "+f"(d[11]), "+f"(d[12]), "+f"(d[13]), "+f"(d[14]), "+f"(d[15]), "+f"(d[16]), "+f"(d[17]), "+f"(d[18]), "+f"(d[19]), "+f"(d[20]), "+f"(d[21]), "+f"(d[22]), "+f"(d[23]), "+f"(d[24]), "+f"(d[25]), "+f"(d[26]), "+f"(d[27]), "+f"(d[28]), "+f"(d[29]), "+f"(d[30]), "+f"(d[31]) : "r"(a[0]), "r"(a[1]), "r"(a[2]), "r"(a[3]), "l"(db), "n"(SD));
}
template<int SD> __device__ __forceinline__ void wgmma_rs_n32(float* d, const uint32_t* a, uint64_t db) {
  asm volatile("{.reg .pred p; setp.ne.b32 p, %21, 0; wgmma.mma_async.sync.aligned.m64n32k16.f32.bf16.bf16 {%0,%1,%2,%3,%4,%5,%6,%7,%8,%9,%10,%11,%12,%13,%14,%15}, {%16,%17,%18,%19}, %20, p, 1, 1, 0;}"
    : "+f"(d[0]), "+f"(d[1]), "+f"(d[2]), "+f"(d[3]), "+f"(d[4]), "+f"(d[5]), "+f"(d[6]), "+f"(d[7]), "+f"(d[8]), "+f"(d[9]), "+f"(d[10]), "+f"(d[11]), "+f"(d[12]), "+f"(d[13]), "+f"(d[14]), "+f"(d[15]) : "r"(a[0]), "r"(a[1]), "r"(a[2]), "r"(a[3]), "l"(db), "n"(SD));
}
template<int SD> __device__ __forceinline__ void wgmma_rs_n40(float* d, const uint32_t* a, uint64_t db) {
  asm volatile("{.reg .pred p; setp.ne.b32 p, %25, 0; wgmma.mma_async.sync.aligned.m64n40k16.f32.bf16.bf16 {%0,%1,%2,%3,%4,%5,%6,%7,%8,%9,%10,%11,%12,%13,%14,%15,%16,%17,%18,%19}, {%20,%21,%22,%23}, %24, p, 1, 1, 0;}"
    : "+f"(d[0]), "+f"(d[1]), "+f"(d[2]), "+f"(d[3]), "+f"(d[4]), "+f"(d[5]), "+f"(d[6]), "+f"(d[7]), "+f"(d[8]), "+f"(d[9]), "+f"(d[10]), "+f"(d[11]), "+f"(d[12]), "+f"(d[13]), "+f"(d[14]), "+f"(d[15]), "+f"(d[16]), "+f"(d[17]), "+f"(d[18]), "+f"(d[19]) : "r"(a[0]), "r"(a[1]), "r"(a[2]), "r"(a[3]), "l"(db), "n"(SD));
}
template<int SD> __device__ __forceinline__ void wgmma_rs_n24_tb(float* d, const uint32_t* a, uint64_t db) {
  asm volatile("{.reg .pred p; setp.ne.b32 p, %17, 0; wgmma.mma_async.sync.aligned.m64n24k16.f32.bf16.bf16 {%0,%1,%2,%3,%4,%5,%6,%7,%8,%9,%10,%11}, {%12,%13,%14,%15}, %16, p, 1, 1, 1;}"
    : "+f"(d[0]), "+f"(d[1]), "+f"(d[2]), "+f"(d[3]), "+f"(d[4]), "+f"(d[5]), "+f"(d[6]), "+f"(d[7]), "+f"(d[8]), "+f"(d[9]), "+f"(d[10]), "+f"(d[11]) : "r"(a[0]), "r"(a[1]), "r"(a[2]), "r"(a[3]), "l"(db), "n"(SD));
}

constexpr uint64_t DESC_SW128 = (uint64_t)1 << 62;
constexpr uint64_t DESC_SW32 = (uint64_t)3 << 62;
__device__ __forceinline__ uint64_t mk_desc(uint64_t sw, uint32_t addr, uint32_t lbo, uint32_t sbo) {
    return sw | ((uint64_t)(sbo >> 4) << 32) | ((uint64_t)(lbo >> 4) << 16) | (uint64_t)((addr & 0x3FFFF) >> 4);
}

constexpr uint32_t SM_BASE = 1024;
constexpr uint32_t P1_STAGE = 40960;
constexpr uint32_t P1_STGA = 98304;
constexpr uint32_t P1_RED = 147456;
constexpr uint32_t AT_Q = 0, AT_K = 16384, AT_V = 81920, AT_TAB = 163840, AT_CT = 230400, AT_ONES = 230912;
constexpr uint32_t P3_O = AT_TAB;
constexpr uint32_t BAR = 229376;
constexpr uint32_t B_FULL = BAR, B_EMPTY = BAR + 32;
constexpr uint32_t B_KV = BAR + 96, B_Q = BAR + 160, B_CONS = BAR + 168, B_WFULL = BAR + 232, B_OFULL = BAR + 296, B_OEMPTY = BAR + 328;
constexpr uint32_t B_STFREE = BAR + 360;
constexpr uint32_t OFF_MAX = BAR + 416, OFF_NORM = BAR + 512;
constexpr int SMEM_BYTES = AT_CT + 1280;
constexpr uint32_t B_STAGED = BAR + 72;
constexpr uint32_t B_TAB = BAR + 64;
constexpr float QSCALE = 0.25f * 1.4426950408889634f;

struct Maps { CUtensorMap xA, xB, wA, wB, o, o16, woA, woB, out; };

__device__ __forceinline__ void phase_qkv(uint8_t* smem, const Maps& mp) {
    constexpr uint32_t sb = SM_BASE;
    const int tid = threadIdx.x, warp = tid >> 5, lane = tid & 31;
    const int nt = blockIdx.x & 7, mt = blockIdx.x >> 3;
    float* sMax = (float*)(smem + OFF_MAX);
    auto produce = [&](int kb) {
        const int s = kb & 3;
        const uint32_t full = sb + B_FULL + 8 * s, st = sb + s * P1_STAGE;
        mbar_expect_tx(full, P1_STAGE);
        tma_load_2d(st, kb < 8 ? &mp.xB : &mp.xA, (kb & 7) * 64, mt * 128, full);
#pragma unroll
        for (int j = 0; j < 3; j++) tma_load_2d(st + 16384 + j * 8192, kb < 8 ? &mp.wB : &mp.wA, j * 512 + nt * 64, (kb & 7) * 64, full);
    };
    if (tid == 0) {
        tma_prefetch_desc(&mp.xB); tma_prefetch_desc(&mp.wB);
        for (int i = 0; i < 4; i++) { mbar_init(sb + B_FULL + 8 * i, 1); mbar_init(sb + B_EMPTY + 8 * i, 2); }
        fence_mbar_init();
        for (int kb = 0; kb < 4; kb++) produce(kb);
        tma_prefetch_desc(&mp.xA); tma_prefetch_desc(&mp.wA);
    }
    if (tid == 32) {
        for (int i = 0; i < 4; i++) mbar_init(sb + B_STFREE + 8 * i, 2);
        mbar_init(sb + B_Q, 1); mbar_init(sb + B_TAB, 256); mbar_init(sb + B_STAGED, 8);
        for (int i = 0; i < 8; i++) { mbar_init(sb + B_KV + 8 * i, 1); mbar_init(sb + B_CONS + 8 * i, 4); mbar_init(sb + B_WFULL + 8 * i, 1); }
        for (int i = 0; i < 4; i++) { mbar_init(sb + B_OFULL + 8 * i, 1); mbar_init(sb + B_OEMPTY + 8 * i, 2); }
        fence_mbar_init();
    }
    if (tid >= 64 && tid < 72) sMax[tid - 64] = 0.f;
    __syncthreads();

    const int wg = __shfl_sync(0xffffffffu, warp >> 2, 0);
    const int branchB = wg < 2;
    const int wh = wg & 1;
    const int kb0 = branchB ? 0 : 8;
    float acc[96];
#pragma unroll
    for (int i = 0; i < 96; i++) acc[i] = 0.f;
    fence_regs(acc);
    if (!branchB) {
        const int w = warp & 7, j = w * 32 + lane;
        const float f = (j + 0.5f) * (1.f / 256.f);
        const uint32_t val = (uint32_t)(__float2int_rn((exp2f(f) - 1.f) * 128.f) - (j >> 1) + (63 << 7) - 0x8000);
        uint4* tb = (uint4*)(smem + AT_TAB) + w * 32 * 8 + lane;
#pragma unroll
        for (int i = 0; i < 8; i++) {
            const uint32_t v = __shfl_sync(0xffffffffu, val, i * 4 + (lane >> 3));
            tb[i * 32] = make_uint4(v, v, v, v);
            if (w < 6) tb[2048 + i * 32] = make_uint4(v << 16, v << 16, v << 16, v << 16);
        }
        if (w == 0) { for (int i = lane; i < 128; i += 32) ((uint32_t*)(smem + AT_ONES))[i] = 0x3F803F80u; }
        if (w == 1) {
            for (int i = lane; i < 64; i += 32) {
                const int r = i >> 3, ww = i & 7, chunk = (ww >> 2) ^ (r >> 2);
                ((uint32_t*)(smem + AT_CT))[i] = (chunk == 0 && (ww & 3) == 0) ? 0x000043A0u : 0u;
            }
        }
        if (w == 2 && lane < 8) ((uint32_t*)(smem + AT_CT + 256))[lane] = lane < 2 ? 0x00003F80u : 0u;
        fence_async_smem();
        mbar_arrive(sb + B_TAB);
        named_bar(3, 512);
    }
    const uint64_t dA0 = mk_desc(DESC_SW128, sb + wh * 8192, 16, 1024);
#pragma unroll
    for (int i = 0; i < 8; i++) {
        const int kb = kb0 + i, s = i & 3;
        mbar_wait(sb + B_FULL + 8 * s, (i >> 2) & 1);
        const uint64_t dA = dA0 + (uint64_t)(s * (P1_STAGE >> 4)), dB = mk_desc(DESC_SW128, sb + s * P1_STAGE + 16384, 8192, 1024);
        wg_fence();
#pragma unroll
        for (int k = 0; k < 4; k++) wgmma_ss_n192_tb(acc, dA + k * 2, dB + k * 128, 1);
        wg_commit();
        if (i == 7 && branchB) asm volatile("bar.arrive 3, 512;" ::: "memory");
        if (i > 0) {
            wg_wait<1>();
            if (i >= 5 && !branchB && (tid & 127) == 0) mbar_arrive(sb + B_STFREE + 8 * (i - 5));
            if (kb + 3 < 16) {
                const uint32_t eb = sb + B_EMPTY + 8 * ((i - 1) & 3);
                if ((tid & 127) == 0) {
                    mbar_arrive(eb);
                    if (wh == 0) { mbar_wait(eb, ((i - 1) >> 2) & 1); produce(kb + 3); }
                }
                __syncwarp();
            }
        }
    }
    wg_wait<0>();
    fence_regs(acc);

    const int wq = warp & 3, g = lane >> 2, t = lane & 3;
    const int lr = (lane & 7) + ((lane >> 3) & 1) * 8;
    const int lc = lane >> 4;
    const int row0 = mt * 128;
    const int w8 = warp & 7;
    if (branchB) {
        {
            const uint32_t eb = sb + B_EMPTY + 8 * 3;
            if ((tid & 127) == 0) {
                mbar_arrive(eb);
                if (wh == 0) { mbar_wait(eb, 1); produce(11); }
            }
            __syncwarp();
        }
        const uint32_t wbuf = sb + AT_TAB + 65536 - 8192 + w8 * 1024;
        const uint32_t stAddr = wbuf + lr * 32 + ((lc ^ ((lr & 7) >> 2)) << 4);
        const uint32_t ooff = (uint32_t)(row0 + wh * 64 + wq * 16) * 32 + lane * 16;
        uint32_t mymax = 0;
#pragma unroll
        for (int sl = 0; sl < 12; sl++) {
            float* a = acc + sl * 8;
            if (sl < 4) {
#pragma unroll
                for (int i = 0; i < 8; i++) a[i] *= QSCALE;
            }
            if (sl < 8) {
                const float n0 = fmaf(a[0], a[0], fmaf(a[1], a[1], fmaf(a[4], a[4], a[5] * a[5])));
                const float n1 = fmaf(a[2], a[2], fmaf(a[3], a[3], fmaf(a[6], a[6], a[7] * a[7])));
                const uint32_t m = __reduce_max_sync(0xffffffffu, __float_as_uint(fmaxf(n0, n1)));
                if (lane == sl) mymax = m;
            }
            stsm_x4(stAddr + (sl & 1) * 512, pack_bf16(a[0], a[1]), pack_bf16(a[2], a[3]), pack_bf16(a[4], a[5]), pack_bf16(a[6], a[7]));
            __syncwarp();
            uint4 val;
            asm volatile("ld.shared.v4.u32 {%0,%1,%2,%3}, [%4];" : "=r"(val.x), "=r"(val.y), "=r"(val.z), "=r"(val.w) : "r"(wbuf + (sl & 1) * 512 + lane * 16) : "memory");
            const int ty = sl >> 2, head = nt * 4 + (sl & 3);
            uint8_t* dst = (uint8_t*)((ty == 0 ? g_qB : (ty == 1 ? g_kB : g_vB)) + (size_t)head * S_LEN * 16);
            *(uint4*)(dst + ooff) = val;
        }
        __syncwarp();
        {
#pragma unroll
            for (int i = 0; i < 2; i++) {
                const int j = 192 + w8 * 8 + i * 4 + (lane >> 3);
                const float f = (j + 0.5f) * (1.f / 256.f);
                const uint32_t v = (uint32_t)(__float2int_rn((exp2f(f) - 1.f) * 128.f) - (j >> 1) + (63 << 7) - 0x8000) << 16;
                *(uint4*)(smem + AT_TAB + 65536 - 8192 + w8 * 1024 + i * 512 + lane * 16) = make_uint4(v, v, v, v);
            }
        }
        if (lane < 8) atomicMax((unsigned int*)&sMax[lane], mymax);
        named_bar(1, 256);
        if (w8 == 7 && lane >= 8 && lane < 16) { const int i = lane - 8; (i < 4 ? g_qn : g_kn)[(nt * 4 + (i & 3)) * 16 + mt] = sMax[i]; }
        named_bar(1, 256);
        const int h = blockIdx.x >> 2, qb = blockIdx.x & 3;
        if (tid == 0) signal_add(&g_cnt.qkvB[nt]);
        auto ld_k = [&](int c) {
            mbar_expect_tx(sb + B_KV + 8 * c, 16384);
            bulk_g2s(sb + AT_K + c * 8192, g_kB + ((size_t)h * S_LEN + c * 256) * 16, 8192, sb + B_KV + 8 * c);
        };
        auto ld_v = [&](int c) { bulk_g2s(sb + AT_V + c * 8192, g_vB + ((size_t)h * S_LEN + c * 256) * 16, 8192, sb + B_KV + 8 * c); };
        if (tid == 32) {
            spin_ge(&g_cnt.qkvB[h >> 2], 16);
            fence_async_all();
            mbar_wait(sb + B_STFREE, 0);
            mbar_expect_tx(sb + B_Q, 16384 + 128);
            bulk_g2s(sb + AT_Q, g_qB + ((size_t)h * S_LEN + qb * 512) * 16, 16384, sb + B_Q);
            ld_k(0);
            bulk_g2s(sb + OFF_NORM, g_qn + h * 16, 64, sb + B_Q);
            bulk_g2s(sb + OFF_NORM + 64, g_kn + h * 16, 64, sb + B_Q);
            mbar_wait(sb + B_STFREE + 16, 0);
            ld_v(0); ld_k(1); ld_v(1);
        }
        __syncwarp();
        mbar_wait(sb + B_STAGED, 0);
        const uint32_t stg = sb + P1_STGA;
#pragma unroll
        for (int sl = 0; sl < 4; sl++)
            *(uint4*)((uint8_t*)(g_qA + ((size_t)(nt * 4 + sl) * S_LEN + row0) * 16) + tid * 16) = *(const uint4*)(smem + P1_STGA + sl * 4096 + tid * 16);
        const int hh = w8 & 3;
        const uint32_t pkb = stg + (4 + hh) * 4096 + wh * 2048, vb = stg + (8 + hh) * 4096 + wh * 2048;
        float kv0[4] = {0.f, 0.f, 0.f, 0.f}, kv1[4] = {0.f, 0.f, 0.f, 0.f}, zz[4] = {0.f, 0.f, 0.f, 0.f};
        const int ar = (lane & 7) + (lane >> 4) * 8, ac = (lane >> 3) & 1;
        const int br = (lane & 7) + ((lane >> 3) & 1) * 8, bc = lane >> 4;
#pragma unroll
        for (int ks = 0; ks < 4; ks++) {
            uint32_t af[4], bf[4];
            ldsm_x4_t(pkb + (ks * 16 + ar) * 32 + ((ac ^ ((ar & 7) >> 2)) << 4), af);
            ldsm_x4_t(vb + (ks * 16 + br) * 32 + ((bc ^ ((br & 7) >> 2)) << 4), bf);
            mma_bf16(kv0, af, bf[0], bf[1]);
            mma_bf16(kv1, af, bf[2], bf[3]);
            mma_bf16(zz, af, 0x3F803F80u, 0x3F803F80u);
        }
        float* rp = (float*)(smem + P1_RED) + hh * 272;
        if (wh == 1) {
            rp[g * 16 + 2 * t] = kv0[0]; rp[g * 16 + 2 * t + 1] = kv0[1];
            rp[(g + 8) * 16 + 2 * t] = kv0[2]; rp[(g + 8) * 16 + 2 * t + 1] = kv0[3];
            rp[g * 16 + 8 + 2 * t] = kv1[0]; rp[g * 16 + 8 + 2 * t + 1] = kv1[1];
            rp[(g + 8) * 16 + 8 + 2 * t] = kv1[2]; rp[(g + 8) * 16 + 8 + 2 * t + 1] = kv1[3];
            if (t == 0) { rp[256 + g] = zz[0]; rp[256 + g + 8] = zz[2]; }
        }
        named_bar(1, 256);
        if (wh == 0) {
            float* gp = g_kvp + (size_t)(mt * NH + nt * 4 + hh) * 272;
            *(float2*)(gp + g * 16 + 2 * t) = make_float2(kv0[0] + rp[g * 16 + 2 * t], kv0[1] + rp[g * 16 + 2 * t + 1]);
            *(float2*)(gp + (g + 8) * 16 + 2 * t) = make_float2(kv0[2] + rp[(g + 8) * 16 + 2 * t], kv0[3] + rp[(g + 8) * 16 + 2 * t + 1]);
            *(float2*)(gp + g * 16 + 8 + 2 * t) = make_float2(kv1[0] + rp[g * 16 + 8 + 2 * t], kv1[1] + rp[g * 16 + 8 + 2 * t + 1]);
            *(float2*)(gp + (g + 8) * 16 + 8 + 2 * t) = make_float2(kv1[2] + rp[(g + 8) * 16 + 8 + 2 * t], kv1[3] + rp[(g + 8) * 16 + 8 + 2 * t + 1]);
            if (t == 0) { gp[256 + g] = zz[0] + rp[256 + g]; gp[256 + g + 8] = zz[2] + rp[256 + g + 8]; }
        }
    } else {
        if ((tid & 127) == 0) mbar_arrive(sb + B_STFREE + 8 * 3);
        named_bar(2, 256);
        const uint32_t stg = sb + P1_STGA;
        const uint32_t stAddr = stg + (wh * 64 + wq * 16 + lr) * 32 + (((lc ^ ((lr & 7) >> 2))) << 4);
#pragma unroll
        for (int sl = 0; sl < 12; sl++) {
            float* a = acc + sl * 8;
            uint32_t p0 = pack_bf16(a[0], a[1]), p1 = pack_bf16(a[2], a[3]), p2 = pack_bf16(a[4], a[5]), p3 = pack_bf16(a[6], a[7]);
            if (sl >= 4 && sl < 8) { p0 = phi_bf16x2(p0); p1 = phi_bf16x2(p1); p2 = phi_bf16x2(p2); p3 = phi_bf16x2(p3); }
            stsm_x4(stAddr + sl * 4096, p0, p1, p2, p3);
        }
        __syncwarp();
        if (lane == 0) mbar_arrive(sb + B_STAGED);
    }
}

constexpr int AT_NT = 64;
constexpr int AT_NP = 32, AT_NP2 = 40;
constexpr float AT_SAFE2 = 56.f * 56.f;

__device__ __forceinline__ uint32_t ex2_tab2(float ya, float yb, uint32_t lane4) {
    const uint32_t a = __float_as_uint(ya), b = __float_as_uint(yb);
    uint32_t aa, ab, ta, tb, L;
    asm("lop3.b32 %0, %1, 0x7F80, %2, 0xEA;" : "=r"(aa) : "r"(a), "r"(lane4));
    asm("lop3.b32 %0, %1, 0x7F80, %2, 0xEA;" : "=r"(ab) : "r"(b), "r"(lane4));
    asm volatile("ld.shared.u32 %0, [%1+%2];" : "=r"(ta) : "r"(aa), "n"(SM_BASE + AT_TAB));
    asm volatile("ld.shared.u32 %0, [%1+%2];" : "=r"(tb) : "r"(ab), "n"(SM_BASE + AT_TAB + 32768));
    asm("prmt.b32 %0, %1, %2, 0x6521;" : "=r"(L) : "r"(a), "r"(b));
    return L + ta + tb;
}
template <int NT, int NP>
__device__ __forceinline__ void att_exp(const float* s, uint32_t* p, uint32_t lane4) {
    constexpr int PP = NP / 4, TOT = NT / 4;
#pragma unroll
    for (int i = 0; i < TOT; i++) {
        const int nb = (i * PP) / TOT, na = ((i + 1) * PP) / TOT;
        if (na != nb) p[nb] = ex2_tab2(s[2 * nb], s[2 * nb + 1], lane4);
        else { const int im = PP + i - nb; p[im] = pack_bf16(ex2f(s[2 * im]), ex2f(s[2 * im + 1])); }
    }
}

__device__ __forceinline__ void mbar_arrive_elect(uint32_t bar) {
    asm volatile("{.reg .pred p;\nelect.sync _|p, 0xffffffff;\n@p mbarrier.arrive.shared::cta.b64 _, [%0];\n}" ::"r"(bar) : "memory");
}
__device__ __forceinline__ void load_wo_elect(const Maps& mp, int branchB, int nt, int c) {
    constexpr uint32_t sb = SM_BASE;
    const CUtensorMap* tm = branchB ? &mp.woB : &mp.woA;
    asm volatile(
        "{.reg .pred p;\n"
        "elect.sync _|p, 0xffffffff;\n"
        "@p mbarrier.arrive.expect_tx.shared::cta.b64 _, [%0], 16384;\n"
        "@p cp.async.bulk.tensor.2d.shared::cluster.global.mbarrier::complete_tx::bytes [%1], [%3, {%4, %6}], [%0];\n"
        "@p cp.async.bulk.tensor.2d.shared::cluster.global.mbarrier::complete_tx::bytes [%2], [%3, {%5, %6}], [%0];\n"
        "}" ::"r"(sb + B_WFULL + 8 * c), "r"(sb + AT_K + c * 8192), "r"(sb + AT_V + c * 8192), "l"(tm), "r"(nt * 128), "r"(nt * 128 + 64), "r"(c * 64)
        : "memory");
}
__device__ __forceinline__ void load_kv_elect(int h, int c) {
    constexpr uint32_t sb = SM_BASE;
    asm volatile(
        "{.reg .pred p;\n"
        "elect.sync _|p, 0xffffffff;\n"
        "@p mbarrier.arrive.expect_tx.shared::cta.b64 _, [%0], 16384;\n"
        "@p cp.async.bulk.shared::cluster.global.mbarrier::complete_tx::bytes [%1], [%3], 8192, [%0];\n"
        "@p cp.async.bulk.shared::cluster.global.mbarrier::complete_tx::bytes [%2], [%4], 8192, [%0];\n"
        "}" ::"r"(sb + B_KV + 8 * c), "r"(sb + AT_K + c * 8192), "r"(sb + AT_V + c * 8192),
        "l"(g_kB + ((size_t)h * S_LEN + c * 256) * 16), "l"(g_vB + ((size_t)h * S_LEN + c * 256) * 16) : "memory");
}
__device__ __forceinline__ void load_wo(const Maps& mp, int branchB, int nt, int c) {
    constexpr uint32_t sb = SM_BASE;
    const CUtensorMap* tm = branchB ? &mp.woB : &mp.woA;
    mbar_expect_tx(sb + B_WFULL + 8 * c, 16384);
    tma_load_2d(sb + AT_K + c * 8192, tm, nt * 128, c * 64, sb + B_WFULL + 8 * c);
    tma_load_2d(sb + AT_V + c * 8192, tm, nt * 128 + 64, c * 64, sb + B_WFULL + 8 * c);
}

__device__ __forceinline__ void phase_attn(uint8_t* smem, const Maps& mp) {
    constexpr uint32_t sb = SM_BASE;
    const int tid = threadIdx.x, warp = (tid >> 5) & 3, lane = tid & 31;
    const int wg = __shfl_sync(0xffffffffu, tid >> 7, 0);
    const int wwarp = __shfl_sync(0xffffffffu, warp, 0);
    const int h = blockIdx.x >> 2, qb = blockIdx.x & 3;
    constexpr int NCH = 8;
    constexpr uint32_t sK = sb + AT_K, sV = sb + AT_V, sQ = sb + AT_Q, sBar = sb + B_KV;

    named_bar(4 + wg, 128);
    mbar_wait(sb + B_TAB, 0);
    mbar_wait(sb + B_Q, 0);
    if (wg < 2) {
        named_bar(1, 256);
        if (wwarp < 3) load_kv_elect(h, 2 + wg * 3 + wwarp);
    }
    __syncwarp();
    bool safe;
    {
        const float* nrm = (const float*)(smem + OFF_NORM);
        const float qv = lane < 4 ? nrm[qb * 4 + lane] : 0.f;
        const float kv = lane < 16 ? nrm[16 + lane] : 0.f;
        const uint32_t qm = __reduce_max_sync(0xffffffffu, __float_as_uint(qv));
        const uint32_t km = __reduce_max_sync(0xffffffffu, __float_as_uint(kv));
        safe = (__uint_as_float(qm) * __uint_as_float(km) * (16.f * 1.05f) < AT_SAFE2);
    }
    const uint64_t dK0 = mk_desc(DESC_SW32, sK, 16, 256);
    const uint64_t dC = mk_desc(DESC_SW32, sb + AT_CT, 16, 0);
    const uint64_t dV0 = mk_desc(DESC_SW32, sV, AT_ONES - AT_V, 256);
    constexpr int64_t VSTEP = 32 - (32 << 16);
    const uint32_t lane4 = lane * 4;
    uint32_t aone[4];
    asm volatile("ld.shared.v4.u32 {%0,%1,%2,%3}, [%4];" : "=r"(aone[0]), "=r"(aone[1]), "=r"(aone[2]), "=r"(aone[3]) : "r"(sb + AT_CT + 256 + ((lane & 3) == 0 ? 0 : 16)));
    const int g = lane >> 2, t = lane & 3;
    constexpr int NT = AT_NT, NP = AT_NP;
    const int oBranch = blockIdx.x >> 6, oNt = blockIdx.x & 3;

#pragma unroll 1
    for (int qi = 0; qi < 2; qi++) {
        const int qt = wg * 2 + qi;
        const int row0 = qb * 512 + qt * 64 + warp * 16;
        uint32_t qa[4];
        ldsm_x4(sQ + (qt * 64 + warp * 16 + (lane & 7) + ((lane >> 3) & 1) * 8) * 32 + ((((lane >> 4) ^ ((lane & 7) >> 2))) << 4), qa);
        float o[12], s[NT / 2];
#pragma unroll
        for (int i = 0; i < 12; i++) o[i] = 0.f;
#pragma unroll
        for (int i = 0; i < NT / 2; i++) s[i] = 0.f;
        fence_regs(o); fence_regs(s);
        if (safe) {
            uint32_t pa[NT / 4], pb[NT / 4];
            auto issue_qk = [&](uint64_t dK, int np) {
                wgmma_rs_n64<0>(s, qa, dK);
                if (np == 32) wgmma_rs_n32<1>(s, aone, dC); else wgmma_rs_n40<1>(s, aone, dC);
            };
            mbar_wait(sBar, 0);
            wg_fence();
            issue_qk(dK0, NP);
            wg_commit();
            wg_wait<0>();
            fence_regs(s);
            att_exp<NT, NP>(s, pa, lane4);
            if (qi == 0 && wg == 0 && wwarp == 0) {
                asm volatile("{.reg .pred p;\nelect.sync _|p, 0xffffffff;\n@p red.release.gpu.global.add.s32 [%0], 1;\n}" ::"l"(&g_cnt.qkvA[blockIdx.x & 7]) : "memory");
            }
            uint64_t dK = dK0, dV = dV0;
            auto step = [&](uint32_t (&pc)[NT / 4], uint32_t (&pn)[NT / 4], bool last, int jt) {
                wg_fence();
                if (!last) { issue_qk(dK + (uint64_t)(jt * NT * 2 + NT * 2), (jt & 1) ? NP : AT_NP2); wg_commit(); }
#pragma unroll
                for (int kk = 0; kk < NT / 16; kk++) wgmma_rs_n24_tb<1>(o, pc + kk * 4, dV + (uint64_t)((int64_t)(jt * (NT / 16) + kk) * VSTEP));
                wg_commit();
                if (!last) {
                    wg_wait<1>();
                    fence_regs(s);
                    if (jt & 1) att_exp<NT, NP>(s, pn, lane4); else att_exp<NT, AT_NP2>(s, pn, lane4);
                }
                if (last || jt == 3) { wg_wait<0>(); fence_regs(pc); fence_regs(o); }
            };
            constexpr int TPC = 256 / NT;
#pragma unroll 1
            for (int cch = 0; cch < NCH; cch++) {
#pragma unroll
                for (int jj = 0; jj < TPC; jj += 2) {
                    step(pa, pb, false, jj);
                    if (jj + 2 == TPC) {
                        if (cch == NCH - 1) break;
                        mbar_wait(sBar + 8 * (cch + 1), 0);
                    }
                    step(pb, pa, false, jj + 1);
                }
                dK += 256 * 2; dV += (uint64_t)(16 * VSTEP);
                if (qi == 1 && wwarp == 0 && cch < NCH - 1) {
                    mbar_arrive_elect(sb + B_CONS + 8 * cch);
                    if (cch >= 1 && wg == ((cch - 1) & 3)) { mbar_wait(sb + B_CONS + 8 * (cch - 1), 0); load_wo_elect(mp, oBranch, oNt, cch - 1); }
                }
            }
            dV -= (uint64_t)(16 * VSTEP);
            step(pb, pa, true, TPC - 1);
            if (qi == 1 && wwarp == 0) {
                mbar_arrive_elect(sb + B_CONS + 8 * 7);
                if (wg == 2) { mbar_wait(sb + B_CONS + 8 * 6, 0); load_wo_elect(mp, oBranch, oNt, 6); }
                if (wg == 3) { mbar_wait(sb + B_CONS + 8 * 7, 0); load_wo_elect(mp, oBranch, oNt, 7); }
            }
        } else {
            if (qi == 0 && tid == 0) signal_add(&g_cnt.qkvA[blockIdx.x & 7]);
            float m0 = -INFINITY, m1 = -INFINITY;
            uint32_t p[NT / 4];
#pragma unroll 1
            for (int j = 0; j < S_LEN / NT; j++) {
                if ((j * NT) % 256 == 0) mbar_wait(sBar + 8 * ((j * NT) / 256), 0);
                wg_fence();
                wgmma_rs_n64<0>(s, qa, dK0 + (uint64_t)(j * NT * 2));
                wg_commit();
                wg_wait<0>();
                fence_regs(s); fence_regs(o);
                float t0 = m0, t1 = m1;
#pragma unroll
                for (int i = 0; i < NT / 2; i += 4) { t0 = fmaxf(t0, fmaxf(s[i], s[i + 1])); t1 = fmaxf(t1, fmaxf(s[i + 2], s[i + 3])); }
                t0 = fmaxf(t0, __shfl_xor_sync(0xffffffffu, t0, 1)); t0 = fmaxf(t0, __shfl_xor_sync(0xffffffffu, t0, 2));
                t1 = fmaxf(t1, __shfl_xor_sync(0xffffffffu, t1, 1)); t1 = fmaxf(t1, __shfl_xor_sync(0xffffffffu, t1, 2));
                const float r0 = ex2f(m0 - t0), r1 = ex2f(m1 - t1);
                m0 = t0; m1 = t1;
#pragma unroll
                for (int i = 0; i < 12; i += 4) { o[i] *= r0; o[i + 1] *= r0; o[i + 2] *= r1; o[i + 3] *= r1; }
#pragma unroll
                for (int i = 0; i < NT / 4; i += 2) {
                    p[i] = pack_bf16(ex2f(s[2 * i] - m0), ex2f(s[2 * i + 1] - m0));
                    p[i + 1] = pack_bf16(ex2f(s[2 * i + 2] - m1), ex2f(s[2 * i + 3] - m1));
                }
                fence_regs(o);
                wg_fence();
#pragma unroll
                for (int kk = 0; kk < NT / 16; kk++) wgmma_rs_n24_tb<1>(o, p + kk * 4, dV0 + (uint64_t)((int64_t)(j * (NT / 16) + kk) * VSTEP));
                wg_commit();
                wg_wait<0>();
                fence_regs(p);
            }
            fence_regs(o);
        }
        const float l0 = 1.f / o[8], l1 = 1.f / o[10];
        uint32_t* op0 = (uint32_t*)(g_o + (size_t)(row0 + g) * 1024 + 512 + h * 16);
        uint32_t* op1 = (uint32_t*)(g_o + (size_t)(row0 + g + 8) * 1024 + 512 + h * 16);
        op0[t] = pack_bf16(o[0] * l0, o[1] * l0);
        op0[4 + t] = pack_bf16(o[4] * l0, o[5] * l0);
        op1[t] = pack_bf16(o[2] * l1, o[3] * l1);
        op1[4 + t] = pack_bf16(o[6] * l1, o[7] * l1);
    }
    named_bar(4 + wg, 128);
    if ((tid & 127) == 0) signal_add(&g_cnt.oB[(qb * 4 + wg) * 8 + (h >> 2)]);
    __syncthreads();
    if (!safe && tid == 0) {
        for (int c = 0; c < 8; c++) load_wo(mp, oBranch, oNt, c);
    }
}

__device__ __forceinline__ void phase_out(uint8_t* smem, const Maps& mp) {
    (void)smem;
    constexpr uint32_t sb = SM_BASE;
    const int tid = threadIdx.x, warp = tid >> 5, lane = tid & 31;
    const int branchB = blockIdx.x >> 6;
    const int mt = (blockIdx.x & 63) >> 2, nt = blockIdx.x & 3;
    const int wg = __shfl_sync(0xffffffffu, warp >> 2, 0);
    if (wg == 2) {
        if (tid < 256 + 32) {
            if (lane == 0) { tma_prefetch_desc(&mp.o); tma_prefetch_desc(&mp.out); }
            const int* cnt = branchB ? &g_cnt.oB[mt * 8 + (lane & 7)] : &g_cnt.oA;
            int next = 0, spins = 0;
            while (next < 8) {
                int v;
                asm volatile("ld.acquire.gpu.global.s32 %0, [%1];" : "=r"(v) : "l"(cnt) : "memory");
                const uint32_t ready = __ballot_sync(0xffffffffu, v >= 4);
                __syncwarp();
                if (lane == 0) {
                    fence_async_all();
                    for (int kb = next; kb < 8 && ((ready >> kb) & 1); kb++) {
                        const int s = kb & 3;
                        if (kb >= 4) mbar_wait(sb + B_OEMPTY + 8 * s, 0);
                        mbar_expect_tx(sb + B_OFULL + 8 * s, 16384);
                        tma_load_2d(sb + P3_O + s * 16384, &mp.o, branchB * 512 + kb * 64, mt * 128, sb + B_OFULL + 8 * s);
                    }
                }
                while (next < 8 && ((ready >> next) & 1)) next++;
                __syncwarp();
                if (++spins > (1 << 22)) __trap();
                if (next < 8) __nanosleep(SPIN_NS);
            }
            if (lane == 0) finish_ticket();
        }
        return;
    }
    if (wg == 3) return;
    float acc[64];
#pragma unroll
    for (int i = 0; i < 64; i++) acc[i] = 0.f;
    fence_regs(acc);
    const uint64_t dA0 = mk_desc(DESC_SW128, sb + P3_O + wg * 8192, 16, 1024);
#pragma unroll
    for (int kb = 0; kb < 8; kb++) {
        const int s = kb & 3;
        mbar_wait(sb + B_WFULL + 8 * kb, 0);
        mbar_wait(sb + B_OFULL + 8 * s, kb >> 2);
        const uint64_t dA = dA0 + (uint64_t)(s * (16384 >> 4));
        const uint64_t dB = mk_desc(DESC_SW128, sb + AT_K + kb * 8192, AT_V - AT_K, 1024);
        wg_fence();
#pragma unroll
        for (int k = 0; k < 4; k++) wgmma_ss_n128_tb(acc, dA + k * 2, dB + k * 128, 1);
        wg_commit();
        if (kb >= 1 && kb <= 4) {
            wg_wait<1>();
            if ((tid & 127) == 0) mbar_arrive(sb + B_OEMPTY + 8 * (kb - 1));
        }
    }
    wg_wait<0>();
    fence_regs(acc);
    const int wq = warp & 3;
    const uint32_t stg = sb + P3_O + wg * 8192;
    const int lr = wq * 16 + (lane & 7) + ((lane >> 3) & 1) * 8, lc = lane >> 4;
#pragma unroll
    for (int j = 0; j < 8; j++) {
        const float* a = acc + j * 8;
        const int chunk = (j & 3) * 2 + lc;
        stsm_x4(stg + (j >> 2) * 16384 + lr * 128 + ((chunk ^ (lr & 7)) << 4),
                pack_bf16(a[0], a[1]), pack_bf16(a[2], a[3]), pack_bf16(a[4], a[5]), pack_bf16(a[6], a[7]));
    }
    fence_async_smem();
    named_bar(4 + wg, 128);
    if ((tid & 127) < 2) {
        const int j = tid & 1;
        tma_store_2d(&mp.out, stg + j * 16384, branchB * 512 + nt * 128 + j * 64, mt * 128 + wg * 64);
        bulk_commit();
        asm volatile("cp.async.bulk.wait_group.read 0;" ::: "memory");
    }
}

__device__ __noinline__ void linattn_mid(uint8_t* smem, int cta, const CUtensorMap* tmO16) {
    constexpr uint32_t sb = SM_BASE;
    const int tid = threadIdx.x, warp = tid >> 5, lane = tid & 31;
    constexpr int NBUF = 4;
    const uint32_t sBar = sb;
    const uint32_t sQ0 = sb + 1024;
    const uint32_t sSt = sQ0 + NBUF * 32768;
    float* skv = (float*)(smem + 1024 + NBUF * 32768 + 65536);
    if (tid == 0) { for (int i = 0; i < NBUF; i++) { mbar_init(sBar + 8 * i, 1); mbar_init(sBar + 64 + 8 * i, 16); } fence_mbar_init(); }
    __syncthreads();
    if (warp == 0 && lane == 0) { spin_ge(&g_cnt.qkvA[2 * cta], 16); spin_ge(&g_cnt.qkvA[2 * cta + 1], 16); }
    __syncthreads();
    if (lane == 0) fence_async_all();
    __syncwarp();
    auto load_chunk = [&](int c, int j) {
        bulk_g2s(sQ0 + (c % NBUF) * 32768 + j * 8192, g_qA + ((size_t)(cta * 8 + (c >> 3) * 4 + j) * S_LEN + (c & 7) * 256) * 16, 8192, sBar + 8 * (c % NBUF));
    };
    if (lane == 0 && warp < NBUF) {
        mbar_expect_tx(sBar + 8 * warp, 32768);
        for (int j = 0; j < 4; j++) load_chunk(warp, j);
    }
    {
        const int hh = tid >> 6, e = tid & 63;
        const float* gp = g_kvp + (size_t)(cta * 8 + hh) * 272 + e * 4;
        const float* gz = g_kvp + (size_t)(cta * 8 + ((tid >> 4) & 7)) * 272 + 256 + (tid & 15);
        float4 v0, v1, v2, v3, v4, v5, v6, v7;
        float z[16];
#define LD4(m) (*(const float4*)(gp + (size_t)(m) * NH * 272))
#define ADD4(a, b) (a).x += (b).x, (a).y += (b).y, (a).z += (b).z, (a).w += (b).w
#pragma unroll
        for (int m = 0; m < 16; m++) z[m] = tid < 128 ? gz[(size_t)m * NH * 272] : 0.f;
        v0 = LD4(0); v1 = LD4(1); v2 = LD4(2); v3 = LD4(3); v4 = LD4(4); v5 = LD4(5); v6 = LD4(6); v7 = LD4(7);
        {
            const float4 w0 = LD4(8), w1 = LD4(9), w2 = LD4(10), w3 = LD4(11), w4 = LD4(12), w5 = LD4(13), w6 = LD4(14), w7 = LD4(15);
            ADD4(v0, w0); ADD4(v1, w1); ADD4(v2, w2); ADD4(v3, w3); ADD4(v4, w4); ADD4(v5, w5); ADD4(v6, w6); ADD4(v7, w7);
        }
        ADD4(v0, v4); ADD4(v1, v5); ADD4(v2, v6); ADD4(v3, v7); ADD4(v0, v2); ADD4(v1, v3); ADD4(v0, v1);
#undef LD4
#undef ADD4
        *(float4*)(skv + hh * 272 + e * 4) = v0;
        const float zs = (((z[0] + z[1]) + (z[2] + z[3])) + ((z[4] + z[5]) + (z[6] + z[7]))) +
                         (((z[8] + z[9]) + (z[10] + z[11])) + ((z[12] + z[13]) + (z[14] + z[15])));
        if (tid < 128) skv[((tid >> 4) & 7) * 272 + 256 + (tid & 15)] = zs;
    }
    __syncthreads();
    if (tid == 511) finish_ticket();
    const int g = lane >> 2, t = lane & 3;
    const int lr = (lane & 7) + ((lane >> 3) & 1) * 8, lc = lane >> 4;
    const uint32_t loff = (warp * 16 + lr) * 32 + ((lc ^ ((lr & 7) >> 2)) << 4);
#pragma unroll 1
    for (int quad = 0; quad < 2; quad++) {
        uint32_t bf[4][6];
#pragma unroll
        for (int j = 0; j < 4; j++) {
            const float* kv = skv + (quad * 4 + j) * 272;
            bf[j][0] = pack_bf16(kv[(2 * t) * 16 + g], kv[(2 * t + 1) * 16 + g]);
            bf[j][1] = pack_bf16(kv[(2 * t + 8) * 16 + g], kv[(2 * t + 9) * 16 + g]);
            bf[j][2] = pack_bf16(kv[(2 * t) * 16 + 8 + g], kv[(2 * t + 1) * 16 + 8 + g]);
            bf[j][3] = pack_bf16(kv[(2 * t + 8) * 16 + 8 + g], kv[(2 * t + 9) * 16 + 8 + g]);
            bf[j][4] = pack_bf16(kv[256 + 2 * t], kv[256 + 2 * t + 1]);
            bf[j][5] = pack_bf16(kv[256 + 2 * t + 8], kv[256 + 2 * t + 9]);
        }
#pragma unroll 1
        for (int rc = 0; rc < 8; rc++) {
            const int c = quad * 8 + rc;
            mbar_wait(sBar + 8 * (c % NBUF), (c / NBUF) & 1);
            const uint32_t qb = sQ0 + (c % NBUF) * 32768 + loff;
            const uint32_t stg = sSt + (c & 1) * 32768 + warp * 2048;
            uint32_t a[4][4];
#pragma unroll
            for (int j = 0; j < 4; j++) ldsm_x4(qb + j * 8192, a[j]);
            __syncwarp();
            if (lane == 0) {
                mbar_arrive(sBar + 64 + 8 * (c % NBUF));
                if (c >= 1 && warp == (c & 15) && c - 1 + NBUF < 16) {
                    const int cp = c - 1;
                    mbar_wait(sBar + 64 + 8 * (cp % NBUF), (cp / NBUF) & 1);
                    mbar_expect_tx(sBar + 8 * (cp % NBUF), 32768);
                    for (int j = 0; j < 4; j++) load_chunk(cp + NBUF, j);
                }
                if (c >= 2) asm volatile("cp.async.bulk.wait_group.read 1;" ::: "memory");
            }
            __syncwarp();
#pragma unroll
            for (int j = 0; j < 4; j++) {
#pragma unroll
                for (int i = 0; i < 4; i++) a[j][i] = phi_bf16x2(a[j][i]);
                float n0[4] = {0.f, 0.f, 0.f, 0.f}, n1[4] = {0.f, 0.f, 0.f, 0.f}, dn[4] = {0.f, 0.f, 0.f, 0.f};
                mma_bf16(n0, a[j], bf[j][0], bf[j][1]);
                mma_bf16(n1, a[j], bf[j][2], bf[j][3]);
                mma_bf16(dn, a[j], bf[j][4], bf[j][5]);
                const float i0 = rcp_fast(dn[0] + 1e-6f), i1 = rcp_fast(dn[2] + 1e-6f);
                stsm_x4(stg + lr * 128 + (((j * 2 + lc) ^ (lr & 7)) << 4),
                        pack_bf16(n0[0] * i0, n0[1] * i0), pack_bf16(n0[2] * i1, n0[3] * i1),
                        pack_bf16(n1[0] * i0, n1[1] * i0), pack_bf16(n1[2] * i1, n1[3] * i1));
            }
            fence_async_smem();
            __syncwarp();
            if (lane == 0) {
                tma_store_2d(tmO16, stg, cta * 128 + quad * 64, rc * 256 + warp * 16);
                bulk_commit();
            }
        }
    }
    if (lane == 0) { bulk_wait0(); fence_async_all(); }
    __syncthreads();
    if (tid == 0) signal_add(&g_cnt.oA);
}

__global__ void __launch_bounds__(512, 1) fused_kernel(const __grid_constant__ Maps mp) {
    extern __shared__ __align__(1024) uint8_t smem[];
    if (smem_u32(smem) != SM_BASE) __trap();
    if (blockIdx.x >= 128) {
        linattn_mid(smem, blockIdx.x - 128, &mp.o16);
    } else {
        phase_qkv(smem, mp);
        phase_attn(smem, mp);
        phase_out(smem, mp);
    }
}

typedef CUresult (*EncodeFn)(CUtensorMap*, CUtensorMapDataType, cuuint32_t, void*, const cuuint64_t*, const cuuint64_t*,
                             const cuuint32_t*, const cuuint32_t*, CUtensorMapInterleave, CUtensorMapSwizzle,
                             CUtensorMapL2promotion, CUtensorMapFloatOOBfill);

void make_map(EncodeFn enc, CUtensorMap* tm, const void* ptr, uint64_t cols, uint64_t rows, uint32_t boxc, uint32_t boxr) {
    cuuint64_t dims[2] = {cols, rows};
    cuuint64_t strides[1] = {cols * 2};
    cuuint32_t box[2] = {boxc, boxr};
    cuuint32_t es[2] = {1, 1};
    enc(tm, CU_TENSOR_MAP_DATA_TYPE_BFLOAT16, 2, const_cast<void*>(ptr), dims, strides, box, es, CU_TENSOR_MAP_INTERLEAVE_NONE,
        CU_TENSOR_MAP_SWIZZLE_128B, CU_TENSOR_MAP_L2_PROMOTION_L2_256B, CU_TENSOR_MAP_FLOAT_OOB_FILL_NONE);
}

struct HostState {
    bool init;
    const void* key[7];
    Maps mp;
};
HostState g_hs;

}

extern "C" void kernel_launch(void* const* d_in, const int* in_sizes, int n_in, void* d_out, int out_size) {
    (void)in_sizes; (void)n_in; (void)out_size;
    HostState& hs = g_hs;
    bool same = hs.init && hs.key[6] == d_out;
    for (int i = 0; i < 6 && same; i++) same = hs.key[i] == d_in[i];
    if (!same) {
        void* fn = nullptr;
        cudaDriverEntryPointQueryResult qr;
        cudaGetDriverEntryPoint("cuTensorMapEncodeTiled", &fn, cudaEnableDefault, &qr);
        EncodeFn enc = (EncodeFn)fn;
        void* po = nullptr;
        cudaGetSymbolAddress(&po, g_o);
        make_map(enc, &hs.mp.xA, d_in[0], 512, 2048, 64, 128);
        make_map(enc, &hs.mp.wA, d_in[1], 1536, 512, 64, 64);
        make_map(enc, &hs.mp.woA, d_in[2], 512, 512, 64, 64);
        make_map(enc, &hs.mp.xB, d_in[3], 512, 2048, 64, 128);
        make_map(enc, &hs.mp.wB, d_in[4], 1536, 512, 64, 64);
        make_map(enc, &hs.mp.woB, d_in[5], 512, 512, 64, 64);
        make_map(enc, &hs.mp.o, po, 1024, 2048, 64, 128);
        make_map(enc, &hs.mp.o16, po, 1024, 2048, 64, 16);
        make_map(enc, &hs.mp.out, d_out, 1024, 2048, 64, 64);
        cudaFuncSetAttribute(fused_kernel, cudaFuncAttributeMaxDynamicSharedMemorySize, SMEM_BYTES);
        cudaFuncSetAttribute(fused_kernel, cudaFuncAttributePreferredSharedMemoryCarveout, 100);
        for (int i = 0; i < 6; i++) hs.key[i] = d_in[i];
        hs.key[6] = d_out;
        hs.init = true;
    }
    fused_kernel<<<132, 512, SMEM_BYTES, cudaStreamPerThread>>>(hs.mp);
}
```

```cpp
#include <cuda_runtime.h>
#include <cuda_bf16.h>
#include <cuda.h>
#include <stdint.h>

namespace {

constexpr int S_LEN = 2048;
constexpr int NH = 32;

__device__ __align__(1024) uint16_t g_qB[NH * S_LEN * 16];
__device__ __align__(1024) uint16_t g_kB[NH * S_LEN * 16];
__device__ __align__(1024) uint16_t g_vB[NH * S_LEN * 16];
__device__ __align__(1024) uint16_t g_qA[NH * S_LEN * 16];
__device__ __align__(1024) uint16_t g_o[S_LEN * 1024];
__device__ __align__(16) float g_kvp[16 * NH * 272];
__device__ __align__(64) float g_qn[NH * 16];
__device__ __align__(64) float g_kn[NH * 16];

struct Counters {
    int qkvB[8];
    int qkvA[8];
    int oB[16 * 8];
    int oA;
    int done;
};
__device__ Counters g_cnt;

__device__ __forceinline__ uint32_t smem_u32(const void* p) { return (uint32_t)__cvta_generic_to_shared(p); }
__device__ __forceinline__ void wg_fence() { asm volatile("wgmma.fence.sync.aligned;" ::: "memory"); }
__device__ __forceinline__ void wg_commit() { asm volatile("wgmma.commit_group.sync.aligned;" ::: "memory"); }
template <int N> __device__ __forceinline__ void wg_wait() { asm volatile("wgmma.wait_group.sync.aligned %0;" ::"n"(N) : "memory"); }
__device__ __forceinline__ void mbar_init(uint32_t bar, uint32_t cnt) { asm volatile("mbarrier.init.shared::cta.b64 [%0], %1;" ::"r"(bar), "r"(cnt)); }
__device__ __forceinline__ void mbar_expect_tx(uint32_t bar, uint32_t bytes) {
    asm volatile("mbarrier.arrive.expect_tx.shared::cta.b64 _, [%0], %1;" ::"r"(bar), "r"(bytes) : "memory");
}
__device__ __forceinline__ void mbar_wait(uint32_t bar, uint32_t parity) {
    asm volatile(
        "{.reg .pred p;\n"
        "WAIT_LOOP:\n"
        "mbarrier.try_wait.parity.shared::cta.b64 p, [%0], %1;\n"
        "@p bra WAIT_DONE;\n"
        "bra WAIT_LOOP;\n"
        "WAIT_DONE:\n}" ::"r"(bar), "r"(parity) : "memory");
}
__device__ __forceinline__ void mbar_arrive(uint32_t bar) { asm volatile("mbarrier.arrive.shared::cta.b64 _, [%0];" ::"r"(bar) : "memory"); }
__device__ __forceinline__ void fence_mbar_init() { asm volatile("fence.mbarrier_init.release.cluster;" ::: "memory"); }
__device__ __forceinline__ void fence_async_smem() { asm volatile("fence.proxy.async.shared::cta;" ::: "memory"); }
constexpr int SPIN_NS = 100;
__device__ __forceinline__ void spin_ge(const int* p, int target) {
    int it = 0;
    while (true) {
        int v;
        asm volatile("ld.acquire.gpu.global.s32 %0, [%1];" : "=r"(v) : "l"(p) : "memory");
        if (v >= target) break;
        if (++it > (1 << 22)) __trap();
        __nanosleep(SPIN_NS);
    }
}
__device__ __forceinline__ void finish_ticket() {
    if (atomicAdd(&g_cnt.done, 1) == (int)gridDim.x - 1) {
        int* c = (int*)&g_cnt;
        for (int i = 0; i < (int)(sizeof(Counters) / sizeof(int)); i++) c[i] = 0;
    }
}
__device__ __forceinline__ void signal_add(int* p) { asm volatile("red.release.gpu.global.add.s32 [%0], 1;" ::"l"(p) : "memory"); }
__device__ __forceinline__ void fence_async_all() { asm volatile("fence.proxy.async.global;" ::: "memory"); }
__device__ __forceinline__ void named_bar(int id, int n) { asm volatile("bar.sync %0, %1;" ::"r"(id), "r"(n) : "memory"); }

__device__ __forceinline__ void bulk_g2s(uint32_t dst, const void* src, uint32_t bytes, uint32_t bar) {
    asm volatile("cp.async.bulk.shared::cluster.global.mbarrier::complete_tx::bytes [%0], [%1], %2, [%3];" ::"r"(dst), "l"(src), "r"(bytes), "r"(bar) : "memory");
}
__device__ __forceinline__ void bulk_commit() { asm volatile("cp.async.bulk.commit_group;" ::: "memory"); }
__device__ __forceinline__ void bulk_wait0() { asm volatile("cp.async.bulk.wait_group 0;" ::: "memory"); }
__device__ __forceinline__ void tma_load_2d(uint32_t dst, const CUtensorMap* tm, int c0, int c1, uint32_t bar) {
    asm volatile("cp.async.bulk.tensor.2d.shared::cluster.global.mbarrier::complete_tx::bytes [%0], [%1, {%3, %4}], [%2];" ::"r"(dst), "l"(tm), "r"(bar), "r"(c0), "r"(c1) : "memory");
}
__device__ __forceinline__ void tma_store_2d(const CUtensorMap* tm, uint32_t src, int c0, int c1) {
    asm volatile("cp.async.bulk.tensor.2d.global.shared::cta.bulk_group [%0, {%2, %3}], [%1];" ::"l"(tm), "r"(src), "r"(c0), "r"(c1) : "memory");
}
__device__ __forceinline__ void tma_prefetch_desc(const CUtensorMap* tm) { asm volatile("prefetch.tensormap [%0];" ::"l"(tm) : "memory"); }

__device__ __forceinline__ uint32_t pack_bf16(float lo, float hi) {
    uint32_t r; asm("cvt.rn.bf16x2.f32 %0, %1, %2;" : "=r"(r) : "f"(hi), "f"(lo)); return r;
}
__device__ __forceinline__ float ex2f(float x) { float r; asm("ex2.approx.ftz.f32 %0, %1;" : "=f"(r) : "f"(x)); return r; }
__device__ __forceinline__ float bf_lo(uint32_t p) { return __uint_as_float(p << 16); }
__device__ __forceinline__ float bf_hi(uint32_t p) { return __uint_as_float(p & 0xFFFF0000u); }
__device__ __forceinline__ void stsm_x4(uint32_t addr, uint32_t r0, uint32_t r1, uint32_t r2, uint32_t r3) {
    asm volatile("stmatrix.sync.aligned.m8n8.x4.shared.b16 [%0], {%1,%2,%3,%4};" ::"r"(addr), "r"(r0), "r"(r1), "r"(r2), "r"(r3) : "memory");
}
__device__ __forceinline__ void ldsm_x4(uint32_t addr, uint32_t* r) {
    asm volatile("ldmatrix.sync.aligned.m8n8.x4.shared.b16 {%0,%1,%2,%3}, [%4];" : "=r"(r[0]), "=r"(r[1]), "=r"(r[2]), "=r"(r[3]) : "r"(addr) : "memory");
}
__device__ __forceinline__ void ldsm_x4_t(uint32_t addr, uint32_t* r) {
    asm volatile("ldmatrix.sync.aligned.m8n8.x4.trans.shared.b16 {%0,%1,%2,%3}, [%4];" : "=r"(r[0]), "=r"(r[1]), "=r"(r[2]), "=r"(r[3]) : "r"(addr) : "memory");
}
__device__ __forceinline__ void mma_bf16(float* d, const uint32_t* a, uint32_t b0, uint32_t b1) {
    asm volatile("mma.sync.aligned.m16n8k16.row.col.f32.bf16.bf16.f32 {%0,%1,%2,%3}, {%4,%5,%6,%7}, {%8,%9}, {%0,%1,%2,%3};"
                 : "+f"(d[0]), "+f"(d[1]), "+f"(d[2]), "+f"(d[3]) : "r"(a[0]), "r"(a[1]), "r"(a[2]), "r"(a[3]), "r"(b0), "r"(b1));
}
__device__ __forceinline__ uint32_t phi_bf16x2(uint32_t p) {
    const float t0 = bf_lo(p), t1 = bf_hi(p);
    const float a0 = fmaf(t0 + fabsf(t0), 0.5f, ex2f((t0 - fabsf(t0)) * 0.7213475204444817f));
    const float a1 = fmaf(t1 + fabsf(t1), 0.5f, ex2f((t1 - fabsf(t1)) * 0.7213475204444817f));
    const uint32_t a = pack_bf16(a0, a1);
    uint32_t r;
    asm("add.rn.bf16x2 %0, %1, %2;" : "=r"(r) : "r"(a), "r"(0x35863586u));
    return r;
}
__device__ __forceinline__ float rcp_fast(float x) { float r; asm("rcp.approx.ftz.f32 %0, %1;" : "=f"(r) : "f"(x)); return r; }
template <typename T, int N> __device__ __forceinline__ void fence_regs(T (&r)[N]) {
#pragma unroll
    for (int i = 0; i < N; i++) {
        if constexpr (sizeof(T) == 4 && T(0.5) != T(0)) asm volatile("" : "+f"(r[i])::"memory");
        else asm volatile("" : "+r"(r[i])::"memory");
    }
}

__device__ __forceinline__ void wgmma_ss_n192_tb(float* d, uint64_t da, uint64_t db, int sd) {
  asm volatile("{.reg .pred p; setp.ne.b32 p, %98, 0; wgmma.mma_async.sync.aligned.m64n192k16.f32.bf16.bf16 {%0,%1,%2,%3,%4,%5,%6,%7,%8,%9,%10,%11,%12,%13,%14,%15,%16,%17,%18,%19,%20,%21,%22,%23,%24,%25,%26,%27,%28,%29,%30,%31,%32,%33,%34,%35,%36,%37,%38,%39,%40,%41,%42,%43,%44,%45,%46,%47,%48,%49,%50,%51,%52,%53,%54,%55,%56,%57,%58,%59,%60,%61,%62,%63,%64,%65,%66,%67,%68,%69,%70,%71,%72,%73,%74,%75,%76,%77,%78,%79,%80,%81,%82,%83,%84,%85,%86,%87,%88,%89,%90,%91,%92,%93,%94,%95}, %96, %97, p, 1, 1, 0, 1;}"
    : "+f"(d[0]), "+f"(d[1]), "+f"(d[2]), "+f"(d[3]), "+f"(d[4]), "+f"(d[5]), "+f"(d[6]), "+f"(d[7]), "+f"(d[8]), "+f"(d[9]), "+f"(d[10]), "+f"(d[11]), "+f"(d[12]), "+f"(d[13]), "+f"(d[14]), "+f"(d[15]), "+f"(d[16]), "+f"(d[17]), "+f"(d[18]), "+f"(d[19]), "+f"(d[20]), "+f"(d[21]), "+f"(d[22]), "+f"(d[23]), "+f"(d[24]), "+f"(d[25]), "+f"(d[26]), "+f"(d[27]), "+f"(d[28]), "+f"(d[29]), "+f"(d[30]), "+f"(d[31]), "+f"(d[32]), "+f"(d[33]), "+f"(d[34]), "+f"(d[35]), "+f"(d[36]), "+f"(d[37]), "+f"(d[38]), "+f"(d[39]), "+f"(d[40]), "+f"(d[41]), "+f"(d[42]), "+f"(d[43]), "+f"(d[44]), "+f"(d[45]), "+f"(d[46]), "+f"(d[47]), "+f"(d[48]), "+f"(d[49]), "+f"(d[50]), "+f"(d[51]), "+f"(d[52]), "+f"(d[53]), "+f"(d[54]), "+f"(d[55]), "+f"(d[56]), "+f"(d[57]), "+f"(d[58]), "+f"(d[59]), "+f"(d[60]), "+f"(d[61]), "+f"(d[62]), "+f"(d[63]), "+f"(d[64]), "+f"(d[65]), "+f"(d[66]), "+f"(d[67]), "+f"(d[68]), "+f"(d[69]), "+f"(d[70]), "+f"(d[71]), "+f"(d[72]), "+f"(d[73]), "+f"(d[74]), "+f"(d[75]), "+f"(d[76]), "+f"(d[77]), "+f"(d[78]), "+f"(d[79]), "+f"(d[80]), "+f"(d[81]), "+f"(d[82]), "+f"(d[83]), "+f"(d[84]), "+f"(d[85]), "+f"(d[86]), "+f"(d[87]), "+f"(d[88]), "+f"(d[89]), "+f"(d[90]), "+f"(d[91]), "+f"(d[92]), "+f"(d[93]), "+f"(d[94]), "+f"(d[95]) : "l"(da), "l"(db), "r"(sd));
}
__device__ __forceinline__ void wgmma_ss_n128_tb(float* d, uint64_t da, uint64_t db, int sd) {
  asm volatile("{.reg .pred p; setp.ne.b32 p, %66, 0; wgmma.mma_async.sync.aligned.m64n128k16.f32.bf16.bf16 {%0,%1,%2,%3,%4,%5,%6,%7,%8,%9,%10,%11,%12,%13,%14,%15,%16,%17,%18,%19,%20,%21,%22,%23,%24,%25,%26,%27,%28,%29,%30,%31,%32,%33,%34,%35,%36,%37,%38,%39,%40,%41,%42,%43,%44,%45,%46,%47,%48,%49,%50,%51,%52,%53,%54,%55,%56,%57,%58,%59,%60,%61,%62,%63}, %64, %65, p, 1, 1, 0, 1;}"
    : "+f"(d[0]), "+f"(d[1]), "+f"(d[2]), "+f"(d[3]), "+f"(d[4]), "+f"(d[5]), "+f"(d[6]), "+f"(d[7]), "+f"(d[8]), "+f"(d[9]), "+f"(d[10]), "+f"(d[11]), "+f"(d[12]), "+f"(d[13]), "+f"(d[14]), "+f"(d[15]), "+f"(d[16]), "+f"(d[17]), "+f"(d[18]), "+f"(d[19]), "+f"(d[20]), "+f"(d[21]), "+f"(d[22]), "+f"(d[23]), "+f"(d[24]), "+f"(d[25]), "+f"(d[26]), "+f"(d[27]), "+f"(d[28]), "+f"(d[29]), "+f"(d[30]), "+f"(d[31]), "+f"(d[32]), "+f"(d[33]), "+f"(d[34]), "+f"(d[35]), "+f"(d[36]), "+f"(d[37]), "+f"(d[38]), "+f"(d[39]), "+f"(d[40]), "+f"(d[41]), "+f"(d[42]), "+f"(d[43]), "+f"(d[44]), "+f"(d[45]), "+f"(d[46]), "+f"(d[47]), "+f"(d[48]), "+f"(d[49]), "+f"(d[50]), "+f"(d[51]), "+f"(d[52]), "+f"(d[53]), "+f"(d[54]), "+f"(d[55]), "+f"(d[56]), "+f"(d[57]), "+f"(d[58]), "+f"(d[59]), "+f"(d[60]), "+f"(d[61]), "+f"(d[62]), "+f"(d[63]) : "l"(da), "l"(db), "r"(sd));
}
template<int SD> __device__ __forceinline__ void wgmma_rs_n64(float* d, const uint32_t* a, uint64_t db) {
  asm volatile("{.reg .pred p; setp.ne.b32 p, %37, 0; wgmma.mma_async.sync.aligned.m64n64k16.f32.bf16.bf16 {%0,%1,%2,%3,%4,%5,%6,%7,%8,%9,%10,%11,%12,%13,%14,%15,%16,%17,%18,%19,%20,%21,%22,%23,%24,%25,%26,%27,%28,%29,%30,%31}, {%32,%33,%34,%35}, %36, p, 1, 1, 0;}"
    : "+f"(d[0]), "+f"(d[1]), "+f"(d[2]), "+f"(d[3]), "+f"(d[4]), "+f"(d[5]), "+f"(d[6]), "+f"(d[7]), "+f"(d[8]), "+f"(d[9]), "+f"(d[10]), "+f"(d[11]), "+f"(d[12]), "+f"(d[13]), "+f"(d[14]), "+f"(d[15]), "+f"(d[16]), "+f"(d[17]), "+f"(d[18]), "+f"(d[19]), "+f"(d[20]), "+f"(d[21]), "+f"(d[22]), "+f"(d[23]), "+f"(d[24]), "+f"(d[25]), "+f"(d[26]), "+f"(d[27]), "+f"(d[28]), "+f"(d[29]), "+f"(d[30]), "+f"(d[31]) : "r"(a[0]), "r"(a[1]), "r"(a[2]), "r"(a[3]), "l"(db), "n"(SD));
}
template<int SD> __device__ __forceinline__ void wgmma_rs_n32(float* d, const uint32_t* a, uint64_t db) {
  asm volatile("{.reg .pred p; setp.ne.b32 p, %21, 0; wgmma.mma_async.sync.aligned.m64n32k16.f32.bf16.bf16 {%0,%1,%2,%3,%4,%5,%6,%7,%8,%9,%10,%11,%12,%13,%14,%15}, {%16,%17,%18,%19}, %20, p, 1, 1, 0;}"
    : "+f"(d[0]), "+f"(d[1]), "+f"(d[2]), "+f"(d[3]), "+f"(d[4]), "+f"(d[5]), "+f"(d[6]), "+f"(d[7]), "+f"(d[8]), "+f"(d[9]), "+f"(d[10]), "+f"(d[11]), "+f"(d[12]), "+f"(d[13]), "+f"(d[14]), "+f"(d[15]) : "r"(a[0]), "r"(a[1]), "r"(a[2]), "r"(a[3]), "l"(db), "n"(SD));
}
template<int SD> __device__ __forceinline__ void wgmma_rs_n40(float* d, const uint32_t* a, uint64_t db) {
  asm volatile("{.reg .pred p; setp.ne.b32 p, %25, 0; wgmma.mma_async.sync.aligned.m64n40k16.f32.bf16.bf16 {%0,%1,%2,%3,%4,%5,%6,%7,%8,%9,%10,%11,%12,%13,%14,%15,%16,%17,%18,%19}, {%20,%21,%22,%23}, %24, p, 1, 1, 0;}"
    : "+f"(d[0]), "+f"(d[1]), "+f"(d[2]), "+f"(d[3]), "+f"(d[4]), "+f"(d[5]), "+f"(d[6]), "+f"(d[7]), "+f"(d[8]), "+f"(d[9]), "+f"(d[10]), "+f"(d[11]), "+f"(d[12]), "+f"(d[13]), "+f"(d[14]), "+f"(d[15]), "+f"(d[16]), "+f"(d[17]), "+f"(d[18]), "+f"(d[19]) : "r"(a[0]), "r"(a[1]), "r"(a[2]), "r"(a[3]), "l"(db), "n"(SD));
}
template<int SD> __device__ __forceinline__ void wgmma_rs_n24_tb(float* d, const uint32_t* a, uint64_t db) {
  asm volatile("{.reg .pred p; setp.ne.b32 p, %17, 0; wgmma.mma_async.sync.aligned.m64n24k16.f32.bf16.bf16 {%0,%1,%2,%3,%4,%5,%6,%7,%8,%9,%10,%11}, {%12,%13,%14,%15}, %16, p, 1, 1, 1;}"
    : "+f"(d[0]), "+f"(d[1]), "+f"(d[2]), "+f"(d[3]), "+f"(d[4]), "+f"(d[5]), "+f"(d[6]), "+f"(d[7]), "+f"(d[8]), "+f"(d[9]), "+f"(d[10]), "+f"(d[11]) : "r"(a[0]), "r"(a[1]), "r"(a[2]), "r"(a[3]), "l"(db), "n"(SD));
}

constexpr uint64_t DESC_SW128 = (uint64_t)1 << 62;
constexpr uint64_t DESC_SW32 = (uint64_t)3 << 62;
__device__ __forceinline__ uint64_t mk_desc(uint64_t sw, uint32_t addr, uint32_t lbo, uint32_t sbo) {
    return sw | ((uint64_t)(sbo >> 4) << 32) | ((uint64_t)(lbo >> 4) << 16) | (uint64_t)((addr & 0x3FFFF) >> 4);
}

constexpr uint32_t SM_BASE = 1024;
constexpr uint32_t P1_STAGE = 40960;
constexpr uint32_t P1_STGA = 98304;
constexpr uint32_t P1_RED = 147456;
constexpr uint32_t AT_Q = 0, AT_K = 16384, AT_V = 81920, AT_TAB = 163840, AT_CT = 230400, AT_ONES = 230912;
constexpr uint32_t P3_O = AT_TAB;
constexpr uint32_t BAR = 229376;
constexpr uint32_t B_FULL = BAR, B_EMPTY = BAR + 32;
constexpr uint32_t B_KV = BAR + 96, B_Q = BAR + 160, B_CONS = BAR + 168, B_WFULL = BAR + 232, B_OFULL = BAR + 296, B_OEMPTY = BAR + 328;
constexpr uint32_t B_STFREE = BAR + 360;
constexpr uint32_t OFF_MAX = BAR + 416, OFF_NORM = BAR + 512;
constexpr int SMEM_BYTES = AT_CT + 1280;
constexpr uint32_t B_TAB = BAR + 64;
constexpr float QSCALE = 0.25f * 1.4426950408889634f;

struct Maps { CUtensorMap xA, xB, wA, wB, o, o16, woA, woB, out; };

__device__ __forceinline__ void phase_qkv(uint8_t* smem, const Maps& mp) {
    constexpr uint32_t sb = SM_BASE;
    const int tid = threadIdx.x, warp = tid >> 5, lane = tid & 31;
    const int nt = blockIdx.x & 7, mt = blockIdx.x >> 3;
    float* sMax = (float*)(smem + OFF_MAX);
    auto produce = [&](int kb) {
        const int s = kb & 3;
        const uint32_t full = sb + B_FULL + 8 * s, st = sb + s * P1_STAGE;
        mbar_expect_tx(full, P1_STAGE);
        tma_load_2d(st, kb < 8 ? &mp.xB : &mp.xA, (kb & 7) * 64, mt * 128, full);
#pragma unroll
        for (int j = 0; j < 3; j++) tma_load_2d(st + 16384 + j * 8192, kb < 8 ? &mp.wB : &mp.wA, j * 512 + nt * 64, (kb & 7) * 64, full);
    };
    if (tid == 0) {
        tma_prefetch_desc(&mp.xB); tma_prefetch_desc(&mp.wB);
        for (int i = 0; i < 4; i++) { mbar_init(sb + B_FULL + 8 * i, 1); mbar_init(sb + B_EMPTY + 8 * i, 2); }
        fence_mbar_init();
        for (int kb = 0; kb < 4; kb++) produce(kb);
        tma_prefetch_desc(&mp.xA); tma_prefetch_desc(&mp.wA);
    }
    if (tid == 32) {
        for (int i = 0; i < 4; i++) mbar_init(sb + B_STFREE + 8 * i, 2);
        mbar_init(sb + B_Q, 1); mbar_init(sb + B_TAB, 256);
        for (int i = 0; i < 8; i++) { mbar_init(sb + B_KV + 8 * i, 1); mbar_init(sb + B_CONS + 8 * i, 4); mbar_init(sb + B_WFULL + 8 * i, 1); }
        for (int i = 0; i < 4; i++) { mbar_init(sb + B_OFULL + 8 * i, 1); mbar_init(sb + B_OEMPTY + 8 * i, 2); }
        fence_mbar_init();
    }
    if (tid >= 64 && tid < 72) sMax[tid - 64] = 0.f;
    __syncthreads();

    const int wg = __shfl_sync(0xffffffffu, warp >> 2, 0);
    const int branchB = wg < 2;
    const int wh = wg & 1;
    const int kb0 = branchB ? 0 : 8;
    float acc[96];
#pragma unroll
    for (int i = 0; i < 96; i++) acc[i] = 0.f;
    fence_regs(acc);
    if (!branchB) {
        const int w = warp & 7, j = w * 32 + lane;
        const float f = (j + 0.5f) * (1.f / 256.f);
        const uint32_t val = (uint32_t)(__float2int_rn((exp2f(f) - 1.f) * 128.f) - (j >> 1) + (63 << 7) - 0x8000);
        uint4* tb = (uint4*)(smem + AT_TAB) + w * 32 * 8 + lane;
#pragma unroll
        for (int i = 0; i < 8; i++) {
            const uint32_t v = __shfl_sync(0xffffffffu, val, i * 4 + (lane >> 3));
            tb[i * 32] = make_uint4(v, v, v, v);
            tb[2048 + i * 32] = make_uint4(v << 16, v << 16, v << 16, v << 16);
        }
        if (w == 0) { for (int i = lane; i < 128; i += 32) ((uint32_t*)(smem + AT_ONES))[i] = 0x3F803F80u; }
        if (w == 1) {
            for (int i = lane; i < 64; i += 32) {
                const int r = i >> 3, ww = i & 7, chunk = (ww >> 2) ^ (r >> 2);
                ((uint32_t*)(smem + AT_CT))[i] = (chunk == 0 && (ww & 3) == 0) ? 0x000043A0u : 0u;
            }
        }
        if (w == 2 && lane < 8) ((uint32_t*)(smem + AT_CT + 256))[lane] = lane < 2 ? 0x00003F80u : 0u;
        fence_async_smem();
        mbar_arrive(sb + B_TAB);
        named_bar(3, 512);
    }
    const uint64_t dA0 = mk_desc(DESC_SW128, sb + wh * 8192, 16, 1024);
#pragma unroll
    for (int i = 0; i < 8; i++) {
        const int kb = kb0 + i, s = i & 3;
        mbar_wait(sb + B_FULL + 8 * s, (i >> 2) & 1);
        const uint64_t dA = dA0 + (uint64_t)(s * (P1_STAGE >> 4)), dB = mk_desc(DESC_SW128, sb + s * P1_STAGE + 16384, 8192, 1024);
        wg_fence();
#pragma unroll
        for (int k = 0; k < 4; k++) wgmma_ss_n192_tb(acc, dA + k * 2, dB + k * 128, 1);
        wg_commit();
        if (i == 7 && branchB) asm volatile("bar.arrive 3, 512;" ::: "memory");
        if (i > 0) {
            wg_wait<1>();
            if (i >= 5 && !branchB && (tid & 127) == 0) mbar_arrive(sb + B_STFREE + 8 * (i - 5));
            if (kb + 3 < 16) {
                const uint32_t eb = sb + B_EMPTY + 8 * ((i - 1) & 3);
                if ((tid & 127) == 0) {
                    mbar_arrive(eb);
                    if (wh == 0) { mbar_wait(eb, ((i - 1) >> 2) & 1); produce(kb + 3); }
                }
                __syncwarp();
            }
        }
    }
    wg_wait<0>();
    fence_regs(acc);

    const int wq = warp & 3, g = lane >> 2, t = lane & 3;
    const int lr = (lane & 7) + ((lane >> 3) & 1) * 8;
    const int lc = lane >> 4;
    const int row0 = mt * 128;
    const int w8 = warp & 7;
    if (branchB) {
        {
            const uint32_t eb = sb + B_EMPTY + 8 * 3;
            if ((tid & 127) == 0) {
                mbar_arrive(eb);
                if (wh == 0) { mbar_wait(eb, 1); produce(11); }
            }
            __syncwarp();
        }
        const int orow = g + (t >> 1) * 8;
        const uint32_t ooff = (uint32_t)(row0 + wh * 64 + wq * 16 + orow) * 32 + (((t & 1) ^ ((orow & 7) >> 2)) << 4);
        const bool o1 = t & 1, o2 = t & 2;
        uint32_t mymax = 0;
#pragma unroll
        for (int sl = 0; sl < 12; sl++) {
            float* a = acc + sl * 8;
            if (sl < 4) {
#pragma unroll
                for (int i = 0; i < 8; i++) a[i] *= QSCALE;
            }
            if (sl < 8) {
                const float n0 = fmaf(a[0], a[0], fmaf(a[1], a[1], fmaf(a[4], a[4], a[5] * a[5])));
                const float n1 = fmaf(a[2], a[2], fmaf(a[3], a[3], fmaf(a[6], a[6], a[7] * a[7])));
                const uint32_t m = __reduce_max_sync(0xffffffffu, __float_as_uint(fmaxf(n0, n1)));
                if (lane == sl) mymax = m;
            }
            const uint32_t w0 = pack_bf16(a[0], a[1]), w2 = pack_bf16(a[2], a[3]), w1 = pack_bf16(a[4], a[5]), w3 = pack_bf16(a[6], a[7]);
            const uint32_t r0 = __shfl_xor_sync(0xffffffffu, o1 ? w0 : w1, 1), r1 = __shfl_xor_sync(0xffffffffu, o1 ? w2 : w3, 1);
            const uint32_t x0 = o1 ? r0 : w0, x1 = o1 ? w1 : r0, y0 = o1 ? r1 : w2, y1 = o1 ? w3 : r1;
            const uint32_t q0 = __shfl_xor_sync(0xffffffffu, o2 ? x0 : y0, 2), q1 = __shfl_xor_sync(0xffffffffu, o2 ? x1 : y1, 2);
            uint4 val;
            val.x = o2 ? q0 : x0; val.y = o2 ? q1 : x1; val.z = o2 ? y0 : q0; val.w = o2 ? y1 : q1;
            const int ty = sl >> 2, head = nt * 4 + (sl & 3);
            uint8_t* dst = (uint8_t*)((ty == 0 ? g_qB : (ty == 1 ? g_kB : g_vB)) + (size_t)head * S_LEN * 16);
            *(uint4*)(dst + ooff) = val;
        }
        if (lane < 8) atomicMax((unsigned int*)&sMax[lane], mymax);
        named_bar(1, 256);
        if (w8 == 7 && lane >= 8 && lane < 16) { const int i = lane - 8; (i < 4 ? g_qn : g_kn)[(nt * 4 + (i & 3)) * 16 + mt] = sMax[i]; }
        named_bar(1, 256);
        const int h = blockIdx.x >> 2, qb = blockIdx.x & 3;
        if (tid == 0) signal_add(&g_cnt.qkvB[nt]);
        auto ld_k = [&](int c) {
            mbar_expect_tx(sb + B_KV + 8 * c, 16384);
            bulk_g2s(sb + AT_K + c * 8192, g_kB + ((size_t)h * S_LEN + c * 256) * 16, 8192, sb + B_KV + 8 * c);
        };
        auto ld_v = [&](int c) { bulk_g2s(sb + AT_V + c * 8192, g_vB + ((size_t)h * S_LEN + c * 256) * 16, 8192, sb + B_KV + 8 * c); };
        if (tid == 32) {
            spin_ge(&g_cnt.qkvB[h >> 2], 16);
            fence_async_all();
            mbar_wait(sb + B_STFREE, 0);
            mbar_expect_tx(sb + B_Q, 16384 + 128);
            bulk_g2s(sb + AT_Q, g_qB + ((size_t)h * S_LEN + qb * 512) * 16, 16384, sb + B_Q);
            ld_k(0);
            bulk_g2s(sb + OFF_NORM, g_qn + h * 16, 64, sb + B_Q);
            bulk_g2s(sb + OFF_NORM + 64, g_kn + h * 16, 64, sb + B_Q);
            mbar_wait(sb + B_STFREE + 16, 0);
            ld_v(0); ld_k(1); ld_v(1);
        }
        __syncwarp();
    } else {
        if ((tid & 127) == 0) mbar_arrive(sb + B_STFREE + 8 * 3);
        named_bar(2, 256);
        const uint32_t stg = sb + P1_STGA;
        const uint32_t stAddr = stg + (wh * 64 + wq * 16 + lr) * 32 + (((lc ^ ((lr & 7) >> 2))) << 4);
#pragma unroll
        for (int sl = 0; sl < 12; sl++) {
            float* a = acc + sl * 8;
            uint32_t p0 = pack_bf16(a[0], a[1]), p1 = pack_bf16(a[2], a[3]), p2 = pack_bf16(a[4], a[5]), p3 = pack_bf16(a[6], a[7]);
            if (sl >= 4 && sl < 8) { p0 = phi_bf16x2(p0); p1 = phi_bf16x2(p1); p2 = phi_bf16x2(p2); p3 = phi_bf16x2(p3); }
            stsm_x4(stAddr + sl * 4096, p0, p1, p2, p3);
        }
        named_bar(2, 256);
#pragma unroll
        for (int sl = 0; sl < 4; sl++)
            *(uint4*)((uint8_t*)(g_qA + ((size_t)(nt * 4 + sl) * S_LEN + row0) * 16) + (tid - 256) * 16) = *(const uint4*)(smem + P1_STGA + sl * 4096 + (tid - 256) * 16);
        const int hh = w8 & 3;
        const uint32_t pkb = stg + (4 + hh) * 4096 + wh * 2048, vb = stg + (8 + hh) * 4096 + wh * 2048;
        float kv0[4] = {0.f, 0.f, 0.f, 0.f}, kv1[4] = {0.f, 0.f, 0.f, 0.f}, zz[4] = {0.f, 0.f, 0.f, 0.f};
        const int ar = (lane & 7) + (lane >> 4) * 8, ac = (lane >> 3) & 1;
        const int br = (lane & 7) + ((lane >> 3) & 1) * 8, bc = lane >> 4;
#pragma unroll
        for (int ks = 0; ks < 4; ks++) {
            uint32_t af[4], bf[4];
            ldsm_x4_t(pkb + (ks * 16 + ar) * 32 + ((ac ^ ((ar & 7) >> 2)) << 4), af);
            ldsm_x4_t(vb + (ks * 16 + br) * 32 + ((bc ^ ((br & 7) >> 2)) << 4), bf);
            mma_bf16(kv0, af, bf[0], bf[1]);
            mma_bf16(kv1, af, bf[2], bf[3]);
            mma_bf16(zz, af, 0x3F803F80u, 0x3F803F80u);
        }
        float* rp = (float*)(smem + P1_RED) + hh * 272;
        if (wh == 1) {
            rp[g * 16 + 2 * t] = kv0[0]; rp[g * 16 + 2 * t + 1] = kv0[1];
            rp[(g + 8) * 16 + 2 * t] = kv0[2]; rp[(g + 8) * 16 + 2 * t + 1] = kv0[3];
            rp[g * 16 + 8 + 2 * t] = kv1[0]; rp[g * 16 + 8 + 2 * t + 1] = kv1[1];
            rp[(g + 8) * 16 + 8 + 2 * t] = kv1[2]; rp[(g + 8) * 16 + 8 + 2 * t + 1] = kv1[3];
            if (t == 0) { rp[256 + g] = zz[0]; rp[256 + g + 8] = zz[2]; }
        }
        named_bar(2, 256);
        if (wh == 0) {
            float* gp = g_kvp + (size_t)(mt * NH + nt * 4 + hh) * 272;
            *(float2*)(gp + g * 16 + 2 * t) = make_float2(kv0[0] + rp[g * 16 + 2 * t], kv0[1] + rp[g * 16 + 2 * t + 1]);
            *(float2*)(gp + (g + 8) * 16 + 2 * t) = make_float2(kv0[2] + rp[(g + 8) * 16 + 2 * t], kv0[3] + rp[(g + 8) * 16 + 2 * t + 1]);
            *(float2*)(gp + g * 16 + 8 + 2 * t) = make_float2(kv1[0] + rp[g * 16 + 8 + 2 * t], kv1[1] + rp[g * 16 + 8 + 2 * t + 1]);
            *(float2*)(gp + (g + 8) * 16 + 8 + 2 * t) = make_float2(kv1[2] + rp[(g + 8) * 16 + 8 + 2 * t], kv1[3] + rp[(g + 8) * 16 + 8 + 2 * t + 1]);
            if (t == 0) { gp[256 + g] = zz[0] + rp[256 + g]; gp[256 + g + 8] = zz[2] + rp[256 + g + 8]; }
        }
    }
}

constexpr int AT_NT = 64;
constexpr int AT_NP = 32, AT_NP2 = 40;
constexpr float AT_SAFE2 = 56.f * 56.f;

__device__ __forceinline__ uint32_t ex2_tab2(float ya, float yb, uint32_t lane4) {
    const uint32_t a = __float_as_uint(ya), b = __float_as_uint(yb);
    uint32_t aa, ab, ta, tb, L;
    asm("lop3.b32 %0, %1, 0x7F80, %2, 0xEA;" : "=r"(aa) : "r"(a), "r"(lane4));
    asm("lop3.b32 %0, %1, 0x7F80, %2, 0xEA;" : "=r"(ab) : "r"(b), "r"(lane4));
    asm volatile("ld.shared.u32 %0, [%1+%2];" : "=r"(ta) : "r"(aa), "n"(SM_BASE + AT_TAB));
    asm volatile("ld.shared.u32 %0, [%1+%2];" : "=r"(tb) : "r"(ab), "n"(SM_BASE + AT_TAB + 32768));
    asm("prmt.b32 %0, %1, %2, 0x6521;" : "=r"(L) : "r"(a), "r"(b));
    return L + ta + tb;
}
template <int NT, int NP>
__device__ __forceinline__ void att_exp(const float* s, uint32_t* p, uint32_t lane4) {
    constexpr int PP = NP / 4, TOT = NT / 4;
#pragma unroll
    for (int i = 0; i < TOT; i++) {
        const int nb = (i * PP) / TOT, na = ((i + 1) * PP) / TOT;
        if (na != nb) p[nb] = ex2_tab2(s[2 * nb], s[2 * nb + 1], lane4);
        else { const int im = PP + i - nb; p[im] = pack_bf16(ex2f(s[2 * im]), ex2f(s[2 * im + 1])); }
    }
}

__device__ __forceinline__ void mbar_arrive_elect(uint32_t bar) {
    asm volatile("{.reg .pred p;\nelect.sync _|p, 0xffffffff;\n@p mbarrier.arrive.shared::cta.b64 _, [%0];\n}" ::"r"(bar) : "memory");
}
__device__ __forceinline__ void load_wo_elect(const Maps& mp, int branchB, int nt, int c) {
    constexpr uint32_t sb = SM_BASE;
    const CUtensorMap* tm = branchB ? &mp.woB : &mp.woA;
    asm volatile(
        "{.reg .pred p;\n"
        "elect.sync _|p, 0xffffffff;\n"
        "@p mbarrier.arrive.expect_tx.shared::cta.b64 _, [%0], 16384;\n"
        "@p cp.async.bulk.tensor.2d.shared::cluster.global.mbarrier::complete_tx::bytes [%1], [%3, {%4, %6}], [%0];\n"
        "@p cp.async.bulk.tensor.2d.shared::cluster.global.mbarrier::complete_tx::bytes [%2], [%3, {%5, %6}], [%0];\n"
        "}" ::"r"(sb + B_WFULL + 8 * c), "r"(sb + AT_K + c * 8192), "r"(sb + AT_V + c * 8192), "l"(tm), "r"(nt * 128), "r"(nt * 128 + 64), "r"(c * 64)
        : "memory");
}
__device__ __forceinline__ void load_kv_elect(int h, int c) {
    constexpr uint32_t sb = SM_BASE;
    asm volatile(
        "{.reg .pred p;\n"
        "elect.sync _|p, 0xffffffff;\n"
        "@p mbarrier.arrive.expect_tx.shared::cta.b64 _, [%0], 16384;\n"
        "@p cp.async.bulk.shared::cluster.global.mbarrier::complete_tx::bytes [%1], [%3], 8192, [%0];\n"
        "@p cp.async.bulk.shared::cluster.global.mbarrier::complete_tx::bytes [%2], [%4], 8192, [%0];\n"
        "}" ::"r"(sb + B_KV + 8 * c), "r"(sb + AT_K + c * 8192), "r"(sb + AT_V + c * 8192),
        "l"(g_kB + ((size_t)h * S_LEN + c * 256) * 16), "l"(g_vB + ((size_t)h * S_LEN + c * 256) * 16) : "memory");
}
__device__ __forceinline__ void load_wo(const Maps& mp, int branchB, int nt, int c) {
    constexpr uint32_t sb = SM_BASE;
    const CUtensorMap* tm = branchB ? &mp.woB : &mp.woA;
    mbar_expect_tx(sb + B_WFULL + 8 * c, 16384);
    tma_load_2d(sb + AT_K + c * 8192, tm, nt * 128, c * 64, sb + B_WFULL + 8 * c);
    tma_load_2d(sb + AT_V + c * 8192, tm, nt * 128 + 64, c * 64, sb + B_WFULL + 8 * c);
}

__device__ __forceinline__ void phase_attn(uint8_t* smem, const Maps& mp) {
    constexpr uint32_t sb = SM_BASE;
    const int tid = threadIdx.x, warp = (tid >> 5) & 3, lane = tid & 31;
    const int wg = __shfl_sync(0xffffffffu, tid >> 7, 0);
    const int wwarp = __shfl_sync(0xffffffffu, warp, 0);
    const int h = blockIdx.x >> 2, qb = blockIdx.x & 3;
    constexpr int NCH = 8;
    constexpr uint32_t sK = sb + AT_K, sV = sb + AT_V, sQ = sb + AT_Q, sBar = sb + B_KV;

    named_bar(4 + wg, 128);
    mbar_wait(sb + B_TAB, 0);
    mbar_wait(sb + B_Q, 0);
    if (wg >= 2) {
        named_bar(2, 256);
        if (wwarp < 3) load_kv_elect(h, 2 + (wg - 2) * 3 + wwarp);
    }
    __syncwarp();
    bool safe;
    {
        const float* nrm = (const float*)(smem + OFF_NORM);
        const float qv = lane < 4 ? nrm[qb * 4 + lane] : 0.f;
        const float kv = lane < 16 ? nrm[16 + lane] : 0.f;
        const uint32_t qm = __reduce_max_sync(0xffffffffu, __float_as_uint(qv));
        const uint32_t km = __reduce_max_sync(0xffffffffu, __float_as_uint(kv));
        safe = (__uint_as_float(qm) * __uint_as_float(km) * (16.f * 1.05f) < AT_SAFE2);
    }
    const uint64_t dK0 = mk_desc(DESC_SW32, sK, 16, 256);
    const uint64_t dC = mk_desc(DESC_SW32, sb + AT_CT, 16, 0);
    const uint64_t dV0 = mk_desc(DESC_SW32, sV, AT_ONES - AT_V, 256);
    constexpr int64_t VSTEP = 32 - (32 << 16);
    const uint32_t lane4 = lane * 4;
    uint32_t aone[4];
    asm volatile("ld.shared.v4.u32 {%0,%1,%2,%3}, [%4];" : "=r"(aone[0]), "=r"(aone[1]), "=r"(aone[2]), "=r"(aone[3]) : "r"(sb + AT_CT + 256 + ((lane & 3) == 0 ? 0 : 16)));
    const int g = lane >> 2, t = lane & 3;
    constexpr int NT = AT_NT, NP = AT_NP;
    const int oBranch = blockIdx.x >> 6, oNt = blockIdx.x & 3;

#pragma unroll 1
    for (int qi = 0; qi < 2; qi++) {
        const int qt = wg * 2 + qi;
        const int row0 = qb * 512 + qt * 64 + warp * 16;
        uint32_t qa[4];
        ldsm_x4(sQ + (qt * 64 + warp * 16 + (lane & 7) + ((lane >> 3) & 1) * 8) * 32 + ((((lane >> 4) ^ ((lane & 7) >> 2))) << 4), qa);
        float o[12], s[NT / 2];
#pragma unroll
        for (int i = 0; i < 12; i++) o[i] = 0.f;
#pragma unroll
        for (int i = 0; i < NT / 2; i++) s[i] = 0.f;
        fence_regs(o); fence_regs(s);
        if (safe) {
            uint32_t pa[NT / 4], pb[NT / 4];
            auto issue_qk = [&](uint64_t dK, int np) {
                wgmma_rs_n64<0>(s, qa, dK);
                if (np == 32) wgmma_rs_n32<1>(s, aone, dC); else wgmma_rs_n40<1>(s, aone, dC);
            };
            mbar_wait(sBar, 0);
            wg_fence();
            issue_qk(dK0, NP);
            wg_commit();
            wg_wait<0>();
            fence_regs(s);
            att_exp<NT, NP>(s, pa, lane4);
            if (qi == 0 && wg == 2 && wwarp == 0) {
                asm volatile("{.reg .pred p;\nelect.sync _|p, 0xffffffff;\n@p red.release.gpu.global.add.s32 [%0], 1;\n}" ::"l"(&g_cnt.qkvA[blockIdx.x & 7]) : "memory");
            }
            uint64_t dK = dK0, dV = dV0;
            auto step = [&](uint32_t (&pc)[NT / 4], uint32_t (&pn)[NT / 4], bool last, int jt) {
                wg_fence();
                if (!last) { issue_qk(dK + (uint64_t)(jt * NT * 2 + NT * 2), (jt & 1) ? NP : AT_NP2); wg_commit(); }
#pragma unroll
                for (int kk = 0; kk < NT / 16; kk++) wgmma_rs_n24_tb<1>(o, pc + kk * 4, dV + (uint64_t)((int64_t)(jt * (NT / 16) + kk) * VSTEP));
                wg_commit();
                if (!last) {
                    wg_wait<1>();
                    fence_regs(s);
                    if (jt & 1) att_exp<NT, NP>(s, pn, lane4); else att_exp<NT, AT_NP2>(s, pn, lane4);
                }
                if (last || jt == 3) { wg_wait<0>(); fence_regs(pc); fence_regs(o); }
            };
            constexpr int TPC = 256 / NT;
#pragma unroll 1
            for (int cch = 0; cch < NCH; cch++) {
#pragma unroll
                for (int jj = 0; jj < TPC; jj += 2) {
                    step(pa, pb, false, jj);
                    if (jj + 2 == TPC) {
                        if (cch == NCH - 1) break;
                        mbar_wait(sBar + 8 * (cch + 1), 0);
                    }
                    step(pb, pa, false, jj + 1);
                }
                dK += 256 * 2; dV += (uint64_t)(16 * VSTEP);
                if (qi == 1 && wwarp == 0 && cch < NCH - 1) {
                    mbar_arrive_elect(sb + B_CONS + 8 * cch);
                    if (cch >= 1 && wg == ((cch - 1) & 3)) { mbar_wait(sb + B_CONS + 8 * (cch - 1), 0); load_wo_elect(mp, oBranch, oNt, cch - 1); }
                }
            }
            dV -= (uint64_t)(16 * VSTEP);
            step(pb, pa, true, TPC - 1);
            if (qi == 1 && wwarp == 0) {
                mbar_arrive_elect(sb + B_CONS + 8 * 7);
                if (wg == 2) { mbar_wait(sb + B_CONS + 8 * 6, 0); load_wo_elect(mp, oBranch, oNt, 6); }
                if (wg == 3) { mbar_wait(sb + B_CONS + 8 * 7, 0); load_wo_elect(mp, oBranch, oNt, 7); }
            }
        } else {
            if (qi == 0 && tid == 256) signal_add(&g_cnt.qkvA[blockIdx.x & 7]);
            float m0 = -INFINITY, m1 = -INFINITY;
            uint32_t p[NT / 4];
#pragma unroll 1
            for (int j = 0; j < S_LEN / NT; j++) {
                if ((j * NT) % 256 == 0) mbar_wait(sBar + 8 * ((j * NT) / 256), 0);
                wg_fence();
                wgmma_rs_n64<0>(s, qa, dK0 + (uint64_t)(j * NT * 2));
                wg_commit();
                wg_wait<0>();
                fence_regs(s); fence_regs(o);
                float t0 = m0, t1 = m1;
#pragma unroll
                for (int i = 0; i < NT / 2; i += 4) { t0 = fmaxf(t0, fmaxf(s[i], s[i + 1])); t1 = fmaxf(t1, fmaxf(s[i + 2], s[i + 3])); }
                t0 = fmaxf(t0, __shfl_xor_sync(0xffffffffu, t0, 1)); t0 = fmaxf(t0, __shfl_xor_sync(0xffffffffu, t0, 2));
                t1 = fmaxf(t1, __shfl_xor_sync(0xffffffffu, t1, 1)); t1 = fmaxf(t1, __shfl_xor_sync(0xffffffffu, t1, 2));
                const float r0 = ex2f(m0 - t0), r1 = ex2f(m1 - t1);
                m0 = t0; m1 = t1;
#pragma unroll
                for (int i = 0; i < 12; i += 4) { o[i] *= r0; o[i + 1] *= r0; o[i + 2] *= r1; o[i + 3] *= r1; }
#pragma unroll
                for (int i = 0; i < NT / 4; i += 2) {
                    p[i] = pack_bf16(ex2f(s[2 * i] - m0), ex2f(s[2 * i + 1] - m0));
                    p[i + 1] = pack_bf16(ex2f(s[2 * i + 2] - m1), ex2f(s[2 * i + 3] - m1));
                }
                fence_regs(o);
                wg_fence();
#pragma unroll
                for (int kk = 0; kk < NT / 16; kk++) wgmma_rs_n24_tb<1>(o, p + kk * 4, dV0 + (uint64_t)((int64_t)(j * (NT / 16) + kk) * VSTEP));
                wg_commit();
                wg_wait<0>();
                fence_regs(p);
            }
            fence_regs(o);
        }
        const float l0 = 1.f / o[8], l1 = 1.f / o[10];
        uint32_t* op0 = (uint32_t*)(g_o + (size_t)(row0 + g) * 1024 + 512 + h * 16);
        uint32_t* op1 = (uint32_t*)(g_o + (size_t)(row0 + g + 8) * 1024 + 512 + h * 16);
        op0[t] = pack_bf16(o[0] * l0, o[1] * l0);
        op0[4 + t] = pack_bf16(o[4] * l0, o[5] * l0);
        op1[t] = pack_bf16(o[2] * l1, o[3] * l1);
        op1[4 + t] = pack_bf16(o[6] * l1, o[7] * l1);
    }
    named_bar(4 + wg, 128);
    if ((tid & 127) == 0) signal_add(&g_cnt.oB[(qb * 4 + wg) * 8 + (h >> 2)]);
    __syncthreads();
    if (!safe && tid == 0) {
        for (int c = 0; c < 8; c++) load_wo(mp, oBranch, oNt, c);
    }
}

__device__ __forceinline__ void phase_out(uint8_t* smem, const Maps& mp) {
    (void)smem;
    constexpr uint32_t sb = SM_BASE;
    const int tid = threadIdx.x, warp = tid >> 5, lane = tid & 31;
    const int branchB = blockIdx.x >> 6;
    const int mt = (blockIdx.x & 63) >> 2, nt = blockIdx.x & 3;
    const int wg = __shfl_sync(0xffffffffu, warp >> 2, 0);
    if (wg == 2) {
        if (tid < 256 + 32) {
            if (lane == 0) { tma_prefetch_desc(&mp.o); tma_prefetch_desc(&mp.out); }
            const int* cnt = branchB ? &g_cnt.oB[mt * 8 + (lane & 7)] : &g_cnt.oA;
            int next = 0, spins = 0;
            while (next < 8) {
                int v;
                asm volatile("ld.acquire.gpu.global.s32 %0, [%1];" : "=r"(v) : "l"(cnt) : "memory");
                const uint32_t ready = __ballot_sync(0xffffffffu, v >= 4);
                __syncwarp();
                if (lane == 0) {
                    fence_async_all();
                    for (int kb = next; kb < 8 && ((ready >> kb) & 1); kb++) {
                        const int s = kb & 3;
                        if (kb >= 4) mbar_wait(sb + B_OEMPTY + 8 * s, 0);
                        mbar_expect_tx(sb + B_OFULL + 8 * s, 16384);
                        tma_load_2d(sb + P3_O + s * 16384, &mp.o, branchB * 512 + kb * 64, mt * 128, sb + B_OFULL + 8 * s);
                    }
                }
                while (next < 8 && ((ready >> next) & 1)) next++;
                __syncwarp();
                if (++spins > (1 << 22)) __trap();
                if (next < 8) __nanosleep(SPIN_NS);
            }
            if (lane == 0) finish_ticket();
        }
        return;
    }
    if (wg == 3) return;
    float acc[64];
#pragma unroll
    for (int i = 0; i < 64; i++) acc[i] = 0.f;
    fence_regs(acc);
    const uint64_t dA0 = mk_desc(DESC_SW128, sb + P3_O + wg * 8192, 16, 1024);
#pragma unroll
    for (int kb = 0; kb < 8; kb++) {
        const int s = kb & 3;
        mbar_wait(sb + B_WFULL + 8 * kb, 0);
        mbar_wait(sb + B_OFULL + 8 * s, kb >> 2);
        const uint64_t dA = dA0 + (uint64_t)(s * (16384 >> 4));
        const uint64_t dB = mk_desc(DESC_SW128, sb + AT_K + kb * 8192, AT_V - AT_K, 1024);
        wg_fence();
#pragma unroll
        for (int k = 0; k < 4; k++) wgmma_ss_n128_tb(acc, dA + k * 2, dB + k * 128, 1);
        wg_commit();
        if (kb >= 1 && kb <= 4) {
            wg_wait<1>();
            if ((tid & 127) == 0) mbar_arrive(sb + B_OEMPTY + 8 * (kb - 1));
        }
    }
    wg_wait<0>();
    fence_regs(acc);
    const int wq = warp & 3;
    const uint32_t stg = sb + P3_O + wg * 8192;
    const int lr = wq * 16 + (lane & 7) + ((lane >> 3) & 1) * 8, lc = lane >> 4;
#pragma unroll
    for (int j = 0; j < 8; j++) {
        const float* a = acc + j * 8;
        const int chunk = (j & 3) * 2 + lc;
        stsm_x4(stg + (j >> 2) * 16384 + lr * 128 + ((chunk ^ (lr & 7)) << 4),
                pack_bf16(a[0], a[1]), pack_bf16(a[2], a[3]), pack_bf16(a[4], a[5]), pack_bf16(a[6], a[7]));
    }
    fence_async_smem();
    named_bar(4 + wg, 128);
    if ((tid & 127) < 2) {
        const int j = tid & 1;
        tma_store_2d(&mp.out, stg + j * 16384, branchB * 512 + nt * 128 + j * 64, mt * 128 + wg * 64);
        bulk_commit();
        asm volatile("cp.async.bulk.wait_group.read 0;" ::: "memory");
    }
}

__device__ __noinline__ void linattn_mid(uint8_t* smem, int cta, const CUtensorMap* tmO16) {
    constexpr uint32_t sb = SM_BASE;
    const int tid = threadIdx.x, warp = tid >> 5, lane = tid & 31;
    constexpr int NBUF = 4;
    const uint32_t sBar = sb;
    const uint32_t sQ0 = sb + 1024;
    const uint32_t sSt = sQ0 + NBUF * 32768;
    float* skv = (float*)(smem + 1024 + NBUF * 32768 + 65536);
    if (tid == 0) { for (int i = 0; i < NBUF; i++) { mbar_init(sBar + 8 * i, 1); mbar_init(sBar + 64 + 8 * i, 16); } fence_mbar_init(); }
    __syncthreads();
    if (warp == 0 && lane == 0) { spin_ge(&g_cnt.qkvA[2 * cta], 16); spin_ge(&g_cnt.qkvA[2 * cta + 1], 16); }
    __syncthreads();
    if (lane == 0) fence_async_all();
    __syncwarp();
    auto load_chunk = [&](int c, int j) {
        bulk_g2s(sQ0 + (c % NBUF) * 32768 + j * 8192, g_qA + ((size_t)(cta * 8 + (c >> 3) * 4 + j) * S_LEN + (c & 7) * 256) * 16, 8192, sBar + 8 * (c % NBUF));
    };
    if (lane == 0 && warp < NBUF) {
        mbar_expect_tx(sBar + 8 * warp, 32768);
        for (int j = 0; j < 4; j++) load_chunk(warp, j);
    }
    {
        const int hh = tid >> 6, e = tid & 63;
        const float* gp = g_kvp + (size_t)(cta * 8 + hh) * 272 + e * 4;
        const float* gz = g_kvp + (size_t)(cta * 8 + ((tid >> 4) & 7)) * 272 + 256 + (tid & 15);
        float4 v0, v1, v2, v3, v4, v5, v6, v7;
        float z[16];
#define LD4(m) (*(const float4*)(gp + (size_t)(m) * NH * 272))
#define ADD4(a, b) (a).x += (b).x, (a).y += (b).y, (a).z += (b).z, (a).w += (b).w
#pragma unroll
        for (int m = 0; m < 16; m++) z[m] = tid < 128 ? gz[(size_t)m * NH * 272] : 0.f;
        v0 = LD4(0); v1 = LD4(1); v2 = LD4(2); v3 = LD4(3); v4 = LD4(4); v5 = LD4(5); v6 = LD4(6); v7 = LD4(7);
        {
            const float4 w0 = LD4(8), w1 = LD4(9), w2 = LD4(10), w3 = LD4(11), w4 = LD4(12), w5 = LD4(13), w6 = LD4(14), w7 = LD4(15);
            ADD4(v0, w0); ADD4(v1, w1); ADD4(v2, w2); ADD4(v3, w3); ADD4(v4, w4); ADD4(v5, w5); ADD4(v6, w6); ADD4(v7, w7);
        }
        ADD4(v0, v4); ADD4(v1, v5); ADD4(v2, v6); ADD4(v3, v7); ADD4(v0, v2); ADD4(v1, v3); ADD4(v0, v1);
#undef LD4
#undef ADD4
        *(float4*)(skv + hh * 272 + e * 4) = v0;
        const float zs = (((z[0] + z[1]) + (z[2] + z[3])) + ((z[4] + z[5]) + (z[6] + z[7]))) +
                         (((z[8] + z[9]) + (z[10] + z[11])) + ((z[12] + z[13]) + (z[14] + z[15])));
        if (tid < 128) skv[((tid >> 4) & 7) * 272 + 256 + (tid & 15)] = zs;
    }
    __syncthreads();
    if (tid == 511) finish_ticket();
    const int g = lane >> 2, t = lane & 3;
    const int lr = (lane & 7) + ((lane >> 3) & 1) * 8, lc = lane >> 4;
    const uint32_t loff = (warp * 16 + lr) * 32 + ((lc ^ ((lr & 7) >> 2)) << 4);
#pragma unroll 1
    for (int quad = 0; quad < 2; quad++) {
        uint32_t bf[4][6];
#pragma unroll
        for (int j = 0; j < 4; j++) {
            const float* kv = skv + (quad * 4 + j) * 272;
            bf[j][0] = pack_bf16(kv[(2 * t) * 16 + g], kv[(2 * t + 1) * 16 + g]);
            bf[j][1] = pack_bf16(kv[(2 * t + 8) * 16 + g], kv[(2 * t + 9) * 16 + g]);
            bf[j][2] = pack_bf16(kv[(2 * t) * 16 + 8 + g], kv[(2 * t + 1) * 16 + 8 + g]);
            bf[j][3] = pack_bf16(kv[(2 * t + 8) * 16 + 8 + g], kv[(2 * t + 9) * 16 + 8 + g]);
            bf[j][4] = pack_bf16(kv[256 + 2 * t], kv[256 + 2 * t + 1]);
            bf[j][5] = pack_bf16(kv[256 + 2 * t + 8], kv[256 + 2 * t + 9]);
        }
#pragma unroll 1
        for (int rc = 0; rc < 8; rc++) {
            const int c = quad * 8 + rc;
            mbar_wait(sBar + 8 * (c % NBUF), (c / NBUF) & 1);
            const uint32_t qb = sQ0 + (c % NBUF) * 32768 + loff;
            const uint32_t stg = sSt + (c & 1) * 32768 + warp * 2048;
            uint32_t a[4][4];
#pragma unroll
            for (int j = 0; j < 4; j++) ldsm_x4(qb + j * 8192, a[j]);
            __syncwarp();
            if (lane == 0) {
                mbar_arrive(sBar + 64 + 8 * (c % NBUF));
                if (c >= 1 && warp == (c & 15) && c - 1 + NBUF < 16) {
                    const int cp = c - 1;
                    mbar_wait(sBar + 64 + 8 * (cp % NBUF), (cp / NBUF) & 1);
                    mbar_expect_tx(sBar + 8 * (cp % NBUF), 32768);
                    for (int j = 0; j < 4; j++) load_chunk(cp + NBUF, j);
                }
                if (c >= 2) asm volatile("cp.async.bulk.wait_group.read 1;" ::: "memory");
            }
            __syncwarp();
#pragma unroll
            for (int j = 0; j < 4; j++) {
#pragma unroll
                for (int i = 0; i < 4; i++) a[j][i] = phi_bf16x2(a[j][i]);
                float n0[4] = {0.f, 0.f, 0.f, 0.f}, n1[4] = {0.f, 0.f, 0.f, 0.f}, dn[4] = {0.f, 0.f, 0.f, 0.f};
                mma_bf16(n0, a[j], bf[j][0], bf[j][1]);
                mma_bf16(n1, a[j], bf[j][2], bf[j][3]);
                mma_bf16(dn, a[j], bf[j][4], bf[j][5]);
                const float i0 = rcp_fast(dn[0] + 1e-6f), i1 = rcp_fast(dn[2] + 1e-6f);
                stsm_x4(stg + lr * 128 + (((j * 2 + lc) ^ (lr & 7)) << 4),
                        pack_bf16(n0[0] * i0, n0[1] * i0), pack_bf16(n0[2] * i1, n0[3] * i1),
                        pack_bf16(n1[0] * i0, n1[1] * i0), pack_bf16(n1[2] * i1, n1[3] * i1));
            }
            fence_async_smem();
            __syncwarp();
            if (lane == 0) {
                tma_store_2d(tmO16, stg, cta * 128 + quad * 64, rc * 256 + warp * 16);
                bulk_commit();
            }
        }
    }
    if (lane == 0) { bulk_wait0(); fence_async_all(); }
    __syncthreads();
    if (tid == 0) signal_add(&g_cnt.oA);
}

__global__ void __launch_bounds__(512, 1) fused_kernel(const __grid_constant__ Maps mp) {
    extern __shared__ __align__(1024) uint8_t smem[];
    if (smem_u32(smem) != SM_BASE) __trap();
    if (blockIdx.x >= 128) {
        linattn_mid(smem, blockIdx.x - 128, &mp.o16);
    } else {
        phase_qkv(smem, mp);
        phase_attn(smem, mp);
        phase_out(smem, mp);
    }
}

typedef CUresult (*EncodeFn)(CUtensorMap*, CUtensorMapDataType, cuuint32_t, void*, const cuuint64_t*, const cuuint64_t*,
                             const cuuint32_t*, const cuuint32_t*, CUtensorMapInterleave, CUtensorMapSwizzle,
                             CUtensorMapL2promotion, CUtensorMapFloatOOBfill);

void make_map(EncodeFn enc, CUtensorMap* tm, const void* ptr, uint64_t cols, uint64_t rows, uint32_t boxc, uint32_t boxr) {
    cuuint64_t dims[2] = {cols, rows};
    cuuint64_t strides[1] = {cols * 2};
    cuuint32_t box[2] = {boxc, boxr};
    cuuint32_t es[2] = {1, 1};
    enc(tm, CU_TENSOR_MAP_DATA_TYPE_BFLOAT16, 2, const_cast<void*>(ptr), dims, strides, box, es, CU_TENSOR_MAP_INTERLEAVE_NONE,
        CU_TENSOR_MAP_SWIZZLE_128B, CU_TENSOR_MAP_L2_PROMOTION_L2_256B, CU_TENSOR_MAP_FLOAT_OOB_FILL_NONE);
}

struct HostState {
    bool init;
    const void* key[7];
    Maps mp;
};
HostState g_hs;

}

extern "C" void kernel_launch(void* const* d_in, const int* in_sizes, int n_in, void* d_out, int out_size) {
    (void)in_sizes; (void)n_in; (void)out_size;
    HostState& hs = g_hs;
    bool same = hs.init && hs.key[6] == d_out;
    for (int i = 0; i < 6 && same; i++) same = hs.key[i] == d_in[i];
    if (!same) {
        void* fn = nullptr;
        cudaDriverEntryPointQueryResult qr;
        cudaGetDriverEntryPoint("cuTensorMapEncodeTiled", &fn, cudaEnableDefault, &qr);
        EncodeFn enc = (EncodeFn)fn;
        void* po = nullptr;
        cudaGetSymbolAddress(&po, g_o);
        make_map(enc, &hs.mp.xA, d_in[0], 512, 2048, 64, 128);
        make_map(enc, &hs.mp.wA, d_in[1], 1536, 512, 64, 64);
        make_map(enc, &hs.mp.woA, d_in[2], 512, 512, 64, 64);
        make_map(enc, &hs.mp.xB, d_in[3], 512, 2048, 64, 128);
        make_map(enc, &hs.mp.wB, d_in[4], 1536, 512, 64, 64);
        make_map(enc, &hs.mp.woB, d_in[5], 512, 512, 64, 64);
        make_map(enc, &hs.mp.o, po, 1024, 2048, 64, 128);
        make_map(enc, &hs.mp.o16, po, 1024, 2048, 64, 16);
        make_map(enc, &hs.mp.out, d_out, 1024, 2048, 64, 64);
        cudaFuncSetAttribute(fused_kernel, cudaFuncAttributeMaxDynamicSharedMemorySize, SMEM_BYTES);
        cudaFuncSetAttribute(fused_kernel, cudaFuncAttributePreferredSharedMemoryCarveout, 100);
        for (int i = 0; i < 6; i++) hs.key[i] = d_in[i];
        hs.key[6] = d_out;
        hs.init = true;
    }
    fused_kernel<<<132, 512, SMEM_BYTES, cudaStreamPerThread>>>(hs.mp);
}
```
